```python
import torch

def _softmax(x, axis=-1):
    return torch.softmax(x, dim=axis)
def _gelu(x):
    return torch.nn.functional.gelu(x, approximate="tanh")
def _silu(x):
    return torch.nn.functional.silu(x)
def _sigmoid(x):
    return torch.sigmoid(x)
def _layernorm(x, axis=-1, eps=1e-5):
    m = x.mean(dim=axis, keepdim=True)
    v = x.var(dim=axis, keepdim=True, unbiased=False)
    return (x - m) / torch.sqrt(v + eps)
def _scatter_add(tgt, idx, src, axis=0):
    return tgt.clone().index_add_(axis, idx, src)
def _segment_sum(src, seg, n):
    out = torch.zeros((n,) + src.shape[1:], dtype=src.dtype)
    return out.index_add_(0, seg, src)
def _pad(x, pw):
    flat = tuple(v for pair in reversed(pw) for v in pair)
    return torch.nn.functional.pad(x, flat)

kernel_name = 'parallel_sum__sliding_block_cached__dense_activation_gelu__decode'

def setup_inputs():

    _w = (lambda a: (lambda t: t.to(torch.bfloat16) if t.is_floating_point() else t)(torch.as_tensor(a)))
    def _A_setup():
        B, Sq, D = 1, 1, 448
        Hq, Hkv, Sk, Dh = 16, 8, 65536, 256
        assert Hq % Hkv == 0, (Hq, Hkv)
        return {
            "x": _w((lambda *s: torch.randn(*s, dtype=torch.bfloat16) * 0.05)(B, Sq, D)),
            "k_cache": _w((lambda *s: torch.randn(*s, dtype=torch.bfloat16) * 3.2)(B, Hkv, Sk, Dh)),
            "v_cache": _w((lambda *s: torch.randn(*s, dtype=torch.bfloat16) * 0.8)(B, Hkv, Sk, Dh)),
            "wq": _w((lambda *s: torch.randn(*s, dtype=torch.bfloat16) * 3.2)(D, Hq * Dh) * (D ** -0.5)),
            "wo": _w((lambda *s: torch.randn(*s, dtype=torch.bfloat16) * 0.8)(Hq * Dh, D) * ((Hq * Dh) ** -0.5)),
        }
    _A_in = _A_setup()

    def _B_setup():
        B, S, D, F = 1, 1, 448, 1792
        return {
            "x": _w((lambda *s: torch.randn(*s, dtype=torch.bfloat16) * 0.05)(B, S, D)),
            "w1": _w((lambda *s: torch.randn(*s, dtype=torch.bfloat16) * 3.2)(D, F) * (D ** -0.5)),
            "b1": _w((lambda *s: torch.randn(*s, dtype=torch.bfloat16) * 3.2)(F) * 0.01),
            "w2": _w((lambda *s: torch.randn(*s, dtype=torch.bfloat16) * 0.2)(F, D) * (F ** -0.5)),
            "b2": _w((lambda *s: torch.randn(*s, dtype=torch.bfloat16) * 0.2)(D) * 0.01),
        }
    _B_in = _B_setup()

    return {
        "A_x": _A_in["x"],
        "A_k_cache": _A_in["k_cache"],
        "A_v_cache": _A_in["v_cache"],
        "A_wq": _A_in["wq"],
        "A_wo": _A_in["wo"],
        "B_x": _B_in["x"],
        "B_w1": _B_in["w1"],
        "B_b1": _B_in["b1"],
        "B_w2": _B_in["w2"],
        "B_b2": _B_in["b2"],
    }

def reference(A_x, A_k_cache, A_v_cache, A_wq, A_wo, B_x, B_w1, B_b1, B_w2, B_b2):
    def _A_ref(x, k_cache, v_cache, wq, wo):
        B, Sq, D = x.shape
        Hq, Dh = 16, 256
        Hkv, Sk = k_cache.shape[1], k_cache.shape[2]
        W = min(4096, max(256, Sk // 4))
        rep = Hq // Hkv
        q = (lambda x, *d: x.permute(*d))((x @ wq).reshape(B, Sq, Hq, Dh), 0, 2, 1, 3)
        k = (lambda x, n, axis: torch.repeat_interleave(x, n, dim=axis))(k_cache[:, :, Sk - W:, :], rep, axis=1)
        v = (lambda x, n, axis: torch.repeat_interleave(x, n, dim=axis))(v_cache[:, :, Sk - W:, :], rep, axis=1)
        scores = torch.einsum("bhqd,bhkd->bhqk", q, k) * (Dh ** -0.5)
        p = _softmax(scores, axis=-1)
        o = torch.einsum("bhqk,bhkd->bhqd", p, v)
        return (lambda x, *d: x.permute(*d))(o, 0, 2, 1, 3).reshape(B, Sq, Hq * Dh) @ wo

    def _B_ref(x, w1, b1, w2, b2):
        h = torch.einsum("bsd,df->bsf", x, w1) + b1
        h = _gelu(h)
        return torch.einsum("bsf,fd->bsd", h, w2) + b2

    x = A_x
    xn = _layernorm(x, axis=-1)
    return x + _A_ref(xn, A_k_cache, A_v_cache, A_wq, A_wo) + _B_ref(xn, B_w1, B_b1, B_w2, B_b2)
```

```cpp
#include <cuda_runtime.h>
#include <cuda_bf16.h>
#include <cuda.h>
#include <stdint.h>

namespace {

constexpr int D_MODEL = 448;
constexpr int FFN = 1792;
constexpr int SK = 65536;
constexpr int WKEYS = 4096;
constexpr int NCTA = 120;
constexpr int TILE = 16384;
constexpr int WT = 14336;
constexpr int NS = 13;
constexpr int NTHREADS = 32 * (1 + 8 + 4);
constexpr int SPIN_LIMIT = 1 << 20;
#define WMAX 12
#define FINW 4
#define KF 2
#define ILV 2

constexpr int IT_K = 4, IT_V = 20, IT_WO = 36, NIT = 40;
constexpr int B_FULL = 0, B_EMPTY = NIT, B_Q = NIT + NS, B_ML = B_Q + 1, B_O = B_Q + 2, B_F = B_Q + 3, NBAR = B_Q + 4;
constexpr int SM_W2 = 2 * TILE;
constexpr int SM_DYN = NS * TILE;

struct Scratch {
    uint32_t hbox[8][256];
    uint32_t fbox[56][64][8];
    uint32_t epoch;
    uint32_t pad[31];
};
__device__ __align__(128) Scratch g_scratch;

struct Params {
    const __nv_bfloat16* x;
    const char* k;
    const __nv_bfloat16* b1;
    const __nv_bfloat16* b2;
    __nv_bfloat16* out;
    Scratch* s;
    uint32_t pace;
    uint32_t t0;
    uint32_t pace_wo;
    uint32_t two;
    uint32_t tpoll;
    uint32_t tw1;
    uint32_t tw2;
    uint32_t pace_w2;
};

__device__ __forceinline__ uint32_t s2u(const void* p) { return (uint32_t)__cvta_generic_to_shared(p); }
__device__ __forceinline__ void mbar_init(uint32_t b, uint32_t c) { asm volatile("mbarrier.init.shared::cta.b64 [%0], %1;" :: "r"(b), "r"(c) : "memory"); }
__device__ __forceinline__ void mbar_fence_init() { asm volatile("fence.mbarrier_init.release.cluster;" ::: "memory"); }
__device__ __forceinline__ void mbar_expect(uint32_t b, uint32_t bytes) { asm volatile("mbarrier.arrive.expect_tx.shared::cta.b64 _, [%0], %1;" :: "r"(b), "r"(bytes) : "memory"); }
__device__ __forceinline__ void mbar_arrive(uint32_t b, uint32_t n) { asm volatile("mbarrier.arrive.shared::cta.b64 _, [%0], %1;" :: "r"(b), "r"(n) : "memory"); }
__device__ __forceinline__ void mbar_wait(uint32_t b, uint32_t ph) {
    asm volatile("{\n.reg .pred p;\nW: mbarrier.try_wait.parity.shared::cta.b64 p, [%0], %1;\n@p bra D;\nbra W;\nD:\n}" :: "r"(b), "r"(ph) : "memory");
}
__device__ __forceinline__ bool mbar_test(uint32_t b) {
    uint32_t r;
    asm volatile("{\n.reg .pred p;\nmbarrier.test_wait.parity.shared::cta.b64 p, [%1], 0;\nselp.u32 %0, 1, 0, p;\n}" : "=r"(r) : "r"(b) : "memory");
    return r;
}
__device__ __forceinline__ void bulk(uint32_t dst, const void* src, uint32_t bytes, uint32_t bar, uint64_t pol) {
    asm volatile("cp.async.bulk.shared::cluster.global.mbarrier::complete_tx::bytes.L2::cache_hint [%0], [%1], %2, [%3], %4;" :: "r"(dst), "l"(src), "r"(bytes), "r"(bar), "l"(pol) : "memory");
}
__device__ __forceinline__ void tma2d(uint32_t dst, const void* tm, int x, int y, uint32_t bar) {
    asm volatile("cp.async.bulk.tensor.2d.shared::cluster.global.mbarrier::complete_tx::bytes [%0], [%1, {%3, %4}], [%2];" :: "r"(dst), "l"(tm), "r"(bar), "r"(x), "r"(y) : "memory");
}
__device__ __forceinline__ void tma2d_h(uint32_t dst, const void* tm, int x, int y, uint32_t bar, uint64_t pol) {
    asm volatile("cp.async.bulk.tensor.2d.shared::cluster.global.mbarrier::complete_tx::bytes.L2::cache_hint [%0], [%1, {%3, %4}], [%2], %5;" :: "r"(dst), "l"(tm), "r"(bar), "r"(x), "r"(y), "l"(pol) : "memory");
}
__device__ __forceinline__ void tma3d_h(uint32_t dst, const void* tm, int x, int y, int z, uint32_t bar, uint64_t pol) {
    asm volatile("cp.async.bulk.tensor.3d.shared::cluster.global.mbarrier::complete_tx::bytes.L2::cache_hint [%0], [%1, {%3, %4, %5}], [%2], %6;" :: "r"(dst), "l"(tm), "r"(bar), "r"(x), "r"(y), "r"(z), "l"(pol) : "memory");
}
__device__ __forceinline__ uint4 ldsm4t(uint32_t a) { uint4 v; asm volatile("ldmatrix.sync.aligned.m8n8.x4.trans.shared.b16 {%0,%1,%2,%3}, [%4];" : "=r"(v.x), "=r"(v.y), "=r"(v.z), "=r"(v.w) : "r"(a)); return v; }
__device__ __forceinline__ uint32_t mapa(uint32_t a, uint32_t r) { uint32_t d; asm("mapa.shared::cluster.u32 %0, %1, %2;" : "=r"(d) : "r"(a), "r"(r)); return d; }
__device__ __forceinline__ void st_async1(uint32_t a, uint32_t x, uint32_t bar) {
    asm volatile("st.async.weak.shared::cluster.mbarrier::complete_tx::bytes.b32 [%0], %1, [%2];" :: "r"(a), "r"(x), "r"(bar) : "memory");
}
__device__ __forceinline__ void st_async2(uint32_t a, float x, float y, uint32_t bar) {
    asm volatile("st.async.weak.shared::cluster.mbarrier::complete_tx::bytes.v2.f32 [%0], {%1, %2}, [%3];" :: "r"(a), "f"(x), "f"(y), "r"(bar) : "memory");
}
__device__ __forceinline__ void st_async4(uint32_t a, float x, float y, float z, float w, uint32_t bar) {
    asm volatile("st.async.weak.shared::cluster.mbarrier::complete_tx::bytes.v4.f32 [%0], {%1, %2, %3, %4}, [%5];" :: "r"(a), "f"(x), "f"(y), "f"(z), "f"(w), "r"(bar) : "memory");
}
__device__ __forceinline__ void cluster_arrive() { asm volatile("barrier.cluster.arrive.relaxed.aligned;" ::: "memory"); }
__device__ __forceinline__ void cluster_wait() { asm volatile("barrier.cluster.wait.aligned;" ::: "memory"); }
__device__ __forceinline__ bool elect() { uint32_t r; asm volatile("{\n.reg .pred p;\nelect.sync _|p, 0xffffffff;\nselp.u32 %0,1,0,p;\n}" : "=r"(r)); return r; }
__device__ __forceinline__ uint32_t clk() { uint32_t t; asm volatile("mov.u32 %0, %clock;" : "=r"(t) :: "memory"); return t; }
__device__ __forceinline__ uint32_t gtime() { uint32_t t; asm volatile("mov.u32 %0, %globaltimer_lo;" : "=r"(t) :: "memory"); return t; }
template <int ID, int N> __device__ __forceinline__ void bar_sync() { asm volatile("bar.sync %0, %1;" :: "n"(ID), "n"(N) : "memory"); }
template <int ID, int N> __device__ __forceinline__ void bar_arrive() { asm volatile("bar.arrive %0, %1;" :: "n"(ID), "n"(N) : "memory"); }
__device__ __forceinline__ uint4 lds128(uint32_t a) { uint4 v; asm volatile("ld.shared.v4.u32 {%0,%1,%2,%3}, [%4];" : "=r"(v.x), "=r"(v.y), "=r"(v.z), "=r"(v.w) : "r"(a)); return v; }
__device__ __forceinline__ float2 lds64f(uint32_t a) { float2 v; asm volatile("ld.shared.v2.f32 {%0,%1}, [%2];" : "=f"(v.x), "=f"(v.y) : "r"(a)); return v; }
__device__ __forceinline__ uint4 ldg_poll(const void* p) { uint4 v; asm volatile("ld.relaxed.gpu.global.v4.u32 {%0,%1,%2,%3}, [%4];" : "=r"(v.x), "=r"(v.y), "=r"(v.z), "=r"(v.w) : "l"(p) : "memory"); return v; }
__device__ __forceinline__ void stg_pub4(void* p, uint32_t a, uint32_t b, uint32_t c, uint32_t d) { asm volatile("st.relaxed.gpu.global.v4.u32 [%0], {%1,%2,%3,%4};" :: "l"(p), "r"(a), "r"(b), "r"(c), "r"(d) : "memory"); }
__device__ __forceinline__ void stg_pub2(void* p, uint32_t a, uint32_t b) { asm volatile("st.relaxed.gpu.global.v2.u32 [%0], {%1,%2};" :: "l"(p), "r"(a), "r"(b) : "memory"); }
__device__ __forceinline__ void stg_pub1(void* p, uint32_t a) { asm volatile("st.relaxed.gpu.global.u32 [%0], %1;" :: "l"(p), "r"(a) : "memory"); }
__device__ __forceinline__ uint32_t bad4(uint4 v, uint32_t tag) { return ((v.x ^ tag) | (v.y ^ tag) | (v.z ^ tag) | (v.w ^ tag)) & 3u; }
__device__ __forceinline__ uint32_t tagf(float f, uint32_t tag) { return (__float_as_uint(f) & ~3u) | tag; }
__device__ __forceinline__ float bflo(uint32_t u) { return __uint_as_float(u << 16); }
__device__ __forceinline__ float bfhi(uint32_t u) { return __uint_as_float(u & 0xffff0000u); }
__device__ __forceinline__ float rbf(float f) { return __bfloat162float(__float2bfloat16_rn(f)); }
__device__ __forceinline__ uint32_t pack_bf(float lo, float hi) { const __nv_bfloat162 r = __floats2bfloat162_rn(lo, hi); return *reinterpret_cast<const uint32_t*>(&r); }
__device__ __forceinline__ void fma8(float* a, uint4 w, float s) {
    a[0] = fmaf(bflo(w.x), s, a[0]); a[1] = fmaf(bfhi(w.x), s, a[1]);
    a[2] = fmaf(bflo(w.y), s, a[2]); a[3] = fmaf(bfhi(w.y), s, a[3]);
    a[4] = fmaf(bflo(w.z), s, a[4]); a[5] = fmaf(bfhi(w.z), s, a[5]);
    a[6] = fmaf(bflo(w.w), s, a[6]); a[7] = fmaf(bfhi(w.w), s, a[7]);
}
template <int N, int M> __device__ __forceinline__ void halve(float* a, int lane) {
    const bool up = lane & M;
#pragma unroll
    for (int i = 0; i < N / 2; i++) {
        float keep = up ? a[i + N / 2] : a[i];
        float send = up ? a[i] : a[i + N / 2];
        a[i] = keep + __shfl_xor_sync(0xffffffffu, send, M);
    }
}
__device__ __forceinline__ void mma16816(float* c, uint32_t a0, uint32_t a1, uint32_t a2, uint32_t a3, uint32_t b0, uint32_t b1) {
    asm volatile("mma.sync.aligned.m16n8k16.row.col.f32.bf16.bf16.f32 {%0,%1,%2,%3}, {%4,%5,%6,%7}, {%8,%9}, {%0,%1,%2,%3};"
                 : "+f"(c[0]), "+f"(c[1]), "+f"(c[2]), "+f"(c[3]) : "r"(a0), "r"(a1), "r"(a2), "r"(a3), "r"(b0), "r"(b1));
}
#define TLREC(i) do { } while (0)

__global__ void __cluster_dims__(8, 1, 1) __launch_bounds__(NTHREADS, 1)
fused_decode_kernel(const __grid_constant__ Params p, const __grid_constant__ CUtensorMap tq,
                    const __grid_constant__ CUtensorMap t1, const __grid_constant__ CUtensorMap t2,
                    const __grid_constant__ CUtensorMap tv, const __grid_constant__ CUtensorMap to) {
    extern __shared__ __align__(1024) char sm[];
    __shared__ __align__(8) uint64_t bars[NBAR];
    __shared__ __align__(16) float xn_s[512];
    __shared__ __align__(16) float red_s[8][64];
    __shared__ __align__(16) uint32_t q_s[256];
    __shared__ __align__(16) float2 sc_s[512];
    __shared__ __align__(16) float2 wmax[8], wsum[8];
    __shared__ __align__(16) float4 ml_s[8];
    __shared__ __align__(16) uint32_t p_s[2][256];
    __shared__ __align__(16) float in_s[8 * 64];
    __shared__ __align__(16) uint32_t h_s[112];
    __shared__ __align__(16) float fin_s[8][4];
    __shared__ float b1_s[40];
    __shared__ uint32_t ep_s;

    const int c = blockIdx.x;
    const int warp = __shfl_sync(0xffffffffu, threadIdx.x >> 5, 0);
    int lane;
    asm volatile("mov.u32 %0, %laneid;" : "=r"(lane));
    const uint32_t bar0 = s2u(bars), sm0 = s2u(sm);
    const int cl = c >> 3, r = c & 7;
    const bool attn = cl < 8;

    if (warp == 0) {
        uint32_t g0 = 0;
        const size_t off = (size_t)cl * ((size_t)SK * 512) + (size_t)(SK - WKEYS) * 512;
        const int u0 = ILV == 0 ? r * 16 : ILV == 1 ? r : (r & 3) ^ ((r >> 2) * 80);
        constexpr int TSH = ILV == 0 ? 0 : ILV == 1 ? 3 : 2;
        uint64_t pol;
        asm volatile("createpolicy.fractional.L2::evict_first.b64 %0, 1.0;" : "=l"(pol));
        if (elect()) {
#pragma unroll
            for (int i = 0; i < 4 + KF; i++) mbar_init(bar0 + (B_FULL + i) * 8, 1);
            mbar_fence_init();
            if (attn) {
#pragma unroll
                for (int i = 0; i < KF; i++) { mbar_expect(bar0 + (IT_K + i) * 8, TILE); bulk(sm0 + (IT_K + i) * TILE, p.k + off + (u0 ^ (i << TSH)) * TILE, TILE, bar0 + (IT_K + i) * 8, pol); }
#pragma unroll
                for (int i = 0; i < 4; i++) { mbar_expect(bar0 + i * 8, TILE); tma2d(sm0 + i * TILE, &tq, c * 64, i * 128, bar0 + i * 8); }
            }
            g0 = gtime();
            TLREC(19);
        }
        __syncwarp();
        bar_arrive<1, NTHREADS>();
        bar_sync<2, 64>();
        cluster_arrive();
        if (elect()) {
            if (attn) {
                asm volatile("prefetch.tensormap [%0];" :: "l"(&tv) : "memory");
                asm volatile("prefetch.tensormap [%0];" :: "l"(&to) : "memory");
                uint32_t target = p.t0 * 16;
                const char* src = p.k + off;
                const int row = cl * SK + (SK - WKEYS);
                int slot = IT_K + KF, ph = 1;
#pragma unroll 1
                for (int it = IT_K + KF; it < NIT; it++) {
                    mbar_wait(bar0 + (B_EMPTY + slot) * 8, ph);
                    if (WMAX < NS - 1 && it >= WMAX) mbar_wait(bar0 + (B_FULL + it - WMAX) * 8, 0);
                    if (it == IT_WO) target = p.two * 16;
                    while ((gtime() - g0) * 16 < target) { }
                    const uint32_t b = bar0 + (B_FULL + it) * 8, dst = sm0 + slot * TILE;
                    if (it < IT_WO) {
                        target += p.pace;
                        mbar_expect(b, TILE);
                        const int tt = u0 ^ (((it - IT_K) & 15) << TSH);
                        if (it < IT_V) bulk(dst, src + tt * TILE, TILE, b, pol);
                        else tma3d_h(dst, &tv, 0, row + tt * 32, 0, b, pol);
                    } else {
                        target += p.pace_wo;
                        mbar_expect(b, WT);
                        tma2d_h(dst, &to, 0, (c * 4 + it - IT_WO) * 112, b, pol);
                    }
                    if (++slot == NS) { slot = 0; ph ^= 1; }
                }
                TLREC(0);
            } else {
                while (gtime() - g0 < p.tw1) { }
                mbar_expect(bar0, 2 * WT);
                tma2d(sm0, &t1, r * 224 + (cl - 8) * 32, 0, bar0);
                tma2d(sm0 + WT, &t1, r * 224 + (cl - 8) * 32, 224, bar0);
                asm volatile("prefetch.tensormap [%0];" :: "l"(&t2) : "memory");
                uint32_t target = p.tw2 * 16;
                while (gtime() - g0 + 600 < p.tw2) __nanosleep(200);
#pragma unroll 1
                for (int i = 0; i < 7; i++) {
                    while ((gtime() - g0) * 16 < target) { }
                    target += p.pace_w2;
                    const uint32_t b = bar0 + (1 + i) * 8;
                    mbar_expect(b, 4096);
                    tma2d(sm0 + SM_W2 + i * 4096, &t2, (cl - 8) * 64, r * 224 + i * 32, b);
                }
                while (gtime() - g0 < p.tpoll) { }
                mbar_arrive(bar0 + 8 * 8, 1);
                TLREC(0);
            }
        }
    } else if (warp <= 8) {
        const int w = warp - 1, t = threadIdx.x - 32;
        {
            const uint32_t* x2 = reinterpret_cast<const uint32_t*>(p.x);
            uint32_t xr[7];
            const uint32_t xm = __ldg(x2 + min(t, 223));
#pragma unroll
            for (int i = 0; i < 7; i++) xr[i] = __ldg(x2 + lane + 32 * i);
            float sum = 0.f;
#pragma unroll
            for (int i = 0; i < 7; i++) sum += bflo(xr[i]) + bfhi(xr[i]);
#pragma unroll
            for (int o = 16; o; o >>= 1) sum += __shfl_xor_sync(0xffffffffu, sum, o);
            const float mean = sum * (1.f / D_MODEL);
            float var = 0.f;
#pragma unroll
            for (int i = 0; i < 7; i++) { float a = bflo(xr[i]) - mean, b = bfhi(xr[i]) - mean; var += a * a + b * b; }
#pragma unroll
            for (int o = 16; o; o >>= 1) var += __shfl_xor_sync(0xffffffffu, var, o);
            const float mb = rbf(mean);
            const float den = rbf(__fsqrt_rn(rbf(rbf(var * (1.f / D_MODEL)) + 1e-5f)));
            if (w < 7) {
                float2 v;
                v.x = rbf(__fdiv_rn(rbf(bflo(xm) - mb), den));
                v.y = rbf(__fdiv_rn(rbf(bfhi(xm) - mb), den));
                *reinterpret_cast<float2*>(&xn_s[2 * t]) = v;
            }
        }
        bar_sync<1, NTHREADS>();
        cluster_arrive();
        const uint32_t tag = (ep_s + 1) & 3u;
        if (t == 0) TLREC(1);

        if (attn) {
            {
                float a[8];
#pragma unroll
                for (int i = 0; i < 8; i++) a[i] = 0.f;
#pragma unroll 1
                for (int b = 0; b < 4; b++) {
                    mbar_wait(bar0 + (B_FULL + b) * 8, 0);
                    const uint32_t base = sm0 + b * TILE + t * 16;
                    const float* xs = &xn_s[b * 128 + (t >> 3)];
                    fma8(a, lds128(base), xs[0]);
                    fma8(a, lds128(base + 4096), xs[32]);
                    if (b < 3) {
                        fma8(a, lds128(base + 8192), xs[64]);
                        fma8(a, lds128(base + 12288), xs[96]);
                    }
                    __syncwarp();
                    if (lane == 0) mbar_arrive(bar0 + (B_EMPTY + b) * 8, 1);
                }
                if (t == 0) TLREC(18);
                halve<8, 16>(a, lane); halve<4, 8>(a, lane);
                *reinterpret_cast<float2*>(&red_s[w][(lane & 7) * 8 + (lane >> 3) * 2]) = make_float2(a[0], a[1]);
                bar_sync<3, 256>();
                float q0 = 0.f, q1 = 0.f;
#pragma unroll
                for (int i = 0; i < 8; i++) { const float2 v = *reinterpret_cast<const float2*>(&red_s[i][2 * lane]); q0 += v.x; q1 += v.y; }
                cluster_wait();
                st_async1(mapa(s2u(&q_s[r * 32 + lane]), w), pack_bf(q0, q1), mapa(bar0 + B_Q * 8, w));
                if (t == 0) TLREC(2);
            }
            {
                mbar_wait(bar0 + B_Q * 8, 0);
                if (t == 0) TLREC(3);
                const int g = lane >> 2, tq4 = lane & 3;
                uint4 qf[8];
#pragma unroll
                for (int i = 0; i < 8; i++) {
                    qf[i] = make_uint4(0, 0, 0, 0);
                    if (g < 2) qf[i] = lds128(s2u(q_s) + g * 512 + i * 64 + tq4 * 16);
                }
                float m0 = -INFINITY, m1 = -INFINITY;
#pragma unroll 1
                for (int i4 = 0; i4 < 4; i4++) {
                    const int tile = (w >> 1) + 4 * i4, it = IT_K + tile;
                    const int slot = it >= NS ? it - NS : it;
                    mbar_wait(bar0 + (B_FULL + it) * 8, 0);
                    float ca[4] = {0.f, 0.f, 0.f, 0.f}, cb[4] = {0.f, 0.f, 0.f, 0.f};
                    const uint32_t base = sm0 + slot * TILE + (w & 1) * 8192 + g * 512 + tq4 * 16;
#pragma unroll
                    for (int i = 0; i < 8; i++) {
                        const uint4 lo = lds128(base + i * 64), hi = lds128(base + 4096 + i * 64);
                        mma16816(ca, lo.x, hi.x, lo.y, hi.y, qf[i].x, qf[i].y);
                        mma16816(cb, lo.z, hi.z, lo.w, hi.w, qf[i].z, qf[i].w);
                    }
                    if (lane == 0) mbar_arrive(bar0 + (B_EMPTY + slot) * 8, 4);
                    if (tq4 == 0) {
                        const float s0 = rbf(ca[0] + cb[0]) * 0.0625f, s1 = rbf(ca[1] + cb[1]) * 0.0625f;
                        const float s2 = rbf(ca[2] + cb[2]) * 0.0625f, s3 = rbf(ca[3] + cb[3]) * 0.0625f;
                        const int key = tile * 32 + (w & 1) * 16 + g;
                        sc_s[key] = make_float2(s0, s1);
                        sc_s[key + 8] = make_float2(s2, s3);
                        m0 = fmaxf(m0, fmaxf(s0, s2)); m1 = fmaxf(m1, fmaxf(s1, s3));
                    }
                }
#pragma unroll
                for (int o = 16; o >= 4; o >>= 1) { m0 = fmaxf(m0, __shfl_xor_sync(0xffffffffu, m0, o)); m1 = fmaxf(m1, __shfl_xor_sync(0xffffffffu, m1, o)); }
                if (lane == 0) wmax[w] = make_float2(m0, m1);
            }
            bar_sync<3, 256>();
            {
                if (t == 0) TLREC(4);
                float m0 = -INFINITY, m1 = -INFINITY;
#pragma unroll
                for (int i = 0; i < 8; i++) { const float2 m = wmax[i]; m0 = fmaxf(m0, m.x); m1 = fmaxf(m1, m.y); }
                float4 s = *reinterpret_cast<const float4*>(&sc_s[2 * t]);
                s.x = exp2f((s.x - m0) * 1.4426950408889634f); s.y = exp2f((s.y - m1) * 1.4426950408889634f);
                s.z = exp2f((s.z - m0) * 1.4426950408889634f); s.w = exp2f((s.w - m1) * 1.4426950408889634f);
                const int pos = (t & ~15) + (t & 3) * 4 + ((t >> 2) & 3);
                p_s[0][pos] = pack_bf(s.x, s.z);
                p_s[1][pos] = pack_bf(s.y, s.w);
                float p0 = s.x + s.z, p1 = s.y + s.w;
#pragma unroll
                for (int o = 16; o; o >>= 1) { p0 += __shfl_xor_sync(0xffffffffu, p0, o); p1 += __shfl_xor_sync(0xffffffffu, p1, o); }
                if (lane == 0) wsum[w] = make_float2(p0, p1);
                bar_sync<3, 256>();
                if (t < 8) {
                    float l0 = 0.f, l1 = 0.f;
#pragma unroll
                    for (int i = 0; i < 8; i++) { const float2 l = wsum[i]; l0 += l.x; l1 += l.y; }
                    st_async4(mapa(s2u(&ml_s[r]), t), m0, m1, l0, l1, mapa(bar0 + B_ML * 8, t));
                }
            }
            const int g = lane >> 2, tq4 = lane & 3;
            {
                float acc[4][4];
#pragma unroll
                for (int i = 0; i < 4; i++) { acc[i][0] = acc[i][1] = acc[i][2] = acc[i][3] = 0.f; }
                const uint32_t lo = sm0 + (w >> 1) * 4096 + ((lane & 7) + 8 * (lane >> 4)) * 128;
                const uint32_t sw = ((w & 1) * 4 + ((lane >> 3) & 1)) ^ (lane & 7);
                const uint32_t pa = s2u(&p_s[g & 1][tq4 * 4]);
                const int dst = (tq4 & 1) * 4 + (w >> 1);
                const uint32_t da = mapa(s2u(&in_s[r * 64 + (w & 1) * 32 + (tq4 >> 1) * 16 + g]), dst), db = mapa(bar0 + B_O * 8, dst);
                float wg = 0.f;
                int slot = IT_V - NS;
#pragma unroll 1
                for (int tile = 0; tile < 16; tile++) {
                    if (tile == 10) {
                        mbar_wait(bar0 + B_ML * 8, 0);
                        const float4 v = ml_s[lane & 7];
                        const float m = (lane & 8) ? v.y : v.x;
                        float M = m;
#pragma unroll
                        for (int o = 4; o; o >>= 1) M = fmaxf(M, __shfl_xor_sync(0xffffffffu, M, o));
                        const float e = exp2f((m - M) * 1.4426950408889634f);
                        float L = ((lane & 8) ? v.w : v.z) * e;
#pragma unroll
                        for (int o = 4; o; o >>= 1) L += __shfl_xor_sync(0xffffffffu, L, o);
                        wg = __shfl_sync(0xffffffffu, __fdividef(e, L), (tq4 & 1) * 8 + r);
                    }
                    const uint4 pf = lds128(pa + tile * 64);
                    const uint32_t base = lo + slot * TILE;
                    mbar_wait(bar0 + (B_FULL + IT_V + tile) * 8, 0);
                    uint4 vf[4];
#pragma unroll
                    for (int i = 0; i < 4; i++) vf[i] = ldsm4t(base + (i >> 1) * 2048 + ((sw ^ (2 * (i & 1))) << 4));
                    mma16816(acc[0], vf[0].x, vf[0].y, vf[0].z, vf[0].w, pf.x, pf.y);
                    mma16816(acc[1], vf[1].x, vf[1].y, vf[1].z, vf[1].w, pf.x, pf.y);
                    mma16816(acc[2], vf[2].x, vf[2].y, vf[2].z, vf[2].w, pf.z, pf.w);
                    mma16816(acc[3], vf[3].x, vf[3].y, vf[3].z, vf[3].w, pf.z, pf.w);
                    if (lane == 0) mbar_arrive(bar0 + (B_EMPTY + slot) * 8, 1);
                    if (++slot == NS) slot = 0;
                }
                if (t == 0) TLREC(5);
                const bool hi = tq4 & 2, h1 = tq4 & 1;
                const float x0 = hi ? acc[1][0] + acc[3][0] : acc[0][0] + acc[2][0], x1 = hi ? acc[1][1] + acc[3][1] : acc[0][1] + acc[2][1];
                const float x2 = hi ? acc[1][2] + acc[3][2] : acc[0][2] + acc[2][2], x3 = hi ? acc[1][3] + acc[3][3] : acc[0][3] + acc[2][3];
                st_async1(da, __float_as_uint((h1 ? x1 : x0) * wg), db);
                st_async1(da + 32, __float_as_uint((h1 ? x3 : x2) * wg), db);
                if (t == 0) TLREC(6);
            }
            if (w < 7) {
                float acc[4][4];
#pragma unroll
                for (int i = 0; i < 4; i++) { acc[i][0] = acc[i][1] = acc[i][2] = acc[i][3] = 0.f; }
                const uint32_t unit = 7 * ((lane & 7) + 8 * (lane >> 4)) + w;
                const uint32_t lo = sm0 + unit * 128, sw = ((lane >> 3) & 1) ^ (unit & 7);
                uint32_t* dstp = &p.s->fbox[w * 8 + 2 * tq4][c][g];
                uint4 wf[4][4];
#pragma unroll
                for (int i = 0; i < 3; i++) {
                    mbar_wait(bar0 + (B_FULL + IT_WO + i) * 8, 0);
#pragma unroll
                    for (int k = 0; k < 4; k++) wf[i][k] = ldsm4t(lo + (IT_WO - 2 * NS + i) * TILE + ((sw ^ (2 * k)) << 4));
                }
                const bool have3 = __all_sync(0xffffffffu, mbar_test(bar0 + (B_FULL + IT_WO + 3) * 8));
                if (have3) {
#pragma unroll
                    for (int k = 0; k < 4; k++) wf[3][k] = ldsm4t(lo + ((sw ^ (2 * k)) << 4));
                }
                mbar_wait(bar0 + B_F * 8, 0);
                const uint4 b0 = lds128(s2u(&q_s[tq4 * 8])), b1 = lds128(s2u(&q_s[tq4 * 8 + 4]));
                const uint32_t bf[8] = {b0.x, b0.y, b0.z, b0.w, b1.x, b1.y, b1.z, b1.w};
#pragma unroll
                for (int i = 0; i < 4; i++) {
                    if (i == 3 && !have3) {
                        mbar_wait(bar0 + (B_FULL + IT_WO + 3) * 8, 0);
#pragma unroll
                        for (int k = 0; k < 4; k++) wf[3][k] = ldsm4t(lo + ((sw ^ (2 * k)) << 4));
                    }
#pragma unroll
                    for (int k = 0; k < 4; k++) mma16816(acc[k], wf[i][k].x, wf[i][k].y, wf[i][k].z, wf[i][k].w, bf[2 * i], bf[2 * i + 1]);
                }
                const float f0 = (tq4 & 2) ? ((tq4 & 1) ? acc[3][0] : acc[2][0]) : ((tq4 & 1) ? acc[1][0] : acc[0][0]);
                const float f1 = (tq4 & 2) ? ((tq4 & 1) ? acc[3][2] : acc[2][2]) : ((tq4 & 1) ? acc[1][2] : acc[0][2]);
                stg_pub1(dstp, tagf(f0, tag));
                stg_pub1(dstp + 64 * 8, tagf(f1, tag));
                if (t == 0) TLREC(9);
            } else {
                mbar_wait(bar0 + B_O * 8, 0);

                float2 ov[8];
#pragma unroll
                for (int i = 0; i < 8; i++) ov[i] = lds64f(s2u(&in_s[i * 64 + 2 * lane]));
                q_s[tq4 * 8 + g] = pack_bf(((ov[0].x + ov[1].x) + (ov[2].x + ov[3].x)) + ((ov[4].x + ov[5].x) + (ov[6].x + ov[7].x)),
                                           ((ov[0].y + ov[1].y) + (ov[2].y + ov[3].y)) + ((ov[4].y + ov[5].y) + (ov[6].y + ov[7].y)));
                __syncwarp();
                if (lane == 0) mbar_arrive(bar0 + B_F * 8, 1);
                if (lane == 0) { TLREC(7); TLREC(8); }
            }
        } else {
            float a[8];
#pragma unroll
            for (int i = 0; i < 8; i++) a[i] = 0.f;
            mbar_wait(bar0, 0);
#pragma unroll 1
            for (int i = 0; i < 7; i++) fma8(a, lds128(sm0 + (t + 256 * i) * 16), xn_s[(t >> 2) + 64 * i]);
            halve<8, 16>(a, lane); halve<4, 8>(a, lane); halve<2, 4>(a, lane);
            red_s[w][(lane & 3) * 8 + (lane >> 2)] = a[0];
            bar_sync<3, 256>();
            if (w == 0) {
                float h = 0.f;
#pragma unroll
                for (int i = 0; i < 8; i++) h += red_s[i][lane];
                h = rbf(rbf(h) + b1_s[lane]);
                const float u = 0.7978845608028654f * (h + 0.044715f * h * h * h);
                stg_pub1(&p.s->hbox[r][(cl - 8) * 32 + lane], __float_as_uint(rbf(0.5f * h * (1.f + tanhf(u)))) | tag);
                if (t == 0) TLREC(2);
            }
            if (t < 56) {
                uint4 v;
                int it = 0;
                do { __nanosleep(1000); v = ldg_poll(&p.s->hbox[r][t * 4]); } while (bad4(v, tag) && ++it < SPIN_LIMIT);
                const int pi = 2 * t, pos = (pi & ~15) + (pi & 3) * 4 + ((pi >> 2) & 3);
                h_s[pos] = __byte_perm(v.x, v.y, 0x7632);
                h_s[pos + 4] = __byte_perm(v.z, v.w, 0x7632);
            }
            bar_sync<3, 256>();
            if (t == 0) TLREC(3);
            float acc[2][4] = {{0.f, 0.f, 0.f, 0.f}, {0.f, 0.f, 0.f, 0.f}};
            const uint32_t base = sm0 + SM_W2 + ((lane & 7) + 16 * ((lane >> 3) & 1) + 8 * (lane >> 4)) * 128 + ((w ^ (lane & 7)) << 4);
            const uint32_t da = mapa(s2u(&in_s[r * 8 + (lane >> 2)]), w), db = mapa(bar0 + B_F * 8, w);
            cluster_wait();
            uint2 hf[7];
            uint4 wf[7];
#pragma unroll
            for (int i = 0; i < 7; i++) hf[i] = *reinterpret_cast<const uint2*>(&h_s[i * 16 + (lane & 3) * 4 + ((lane >> 2) & 1) * 2]);
#pragma unroll
            for (int i = 0; i < 8; i++) {
                if (i < 7) { mbar_wait(bar0 + (1 + i) * 8, 0); wf[i] = ldsm4t(base + i * 4096); }
                if (i > 0) mma16816(acc[i & 1], wf[i - 1].x, wf[i - 1].y, wf[i - 1].z, wf[i - 1].w, hf[i - 1].x, hf[i - 1].y);
            }
            if ((lane & 3) == 0) st_async1(da, __float_as_uint((acc[0][0] + acc[0][3]) + (acc[1][0] + acc[1][3])), db);
            if (t == 0) TLREC(9);
            if (w == 0) {
                const int oc = c - 64;
                float base = b1_s[32 + (lane & 7)];
                mbar_wait(bar0 + B_F * 8, 0);
#pragma unroll
                for (int i = 0; i < 8; i++) base += in_s[i * 8 + (lane & 7)];
                bar_sync<4, 160>();
                const float4 u = *reinterpret_cast<const float4*>(&fin_s[lane & 7][0]);
                base += (u.x + u.y) + (u.z + u.w);
                if (lane < 8) p.out[oc * 8 + lane] = __float2bfloat16_rn(base);
                if (oc == 0 && lane == 0) p.s->epoch = ep_s + 1;
                if (t == 0) TLREC(11);
            }
        }
    } else {
        const int fw = warp - 9, t = threadIdx.x - 288;
        if (fw == 0) {
            if (elect()) {
#pragma unroll
                for (int i = 4 + KF; i < NBAR; i++) mbar_init(bar0 + i * 8, (i >= B_EMPTY && i < B_Q) ? 8 : 1);
                mbar_fence_init();
                mbar_expect(bar0 + B_Q * 8, 1024);
                mbar_expect(bar0 + B_ML * 8, 128);
                mbar_expect(bar0 + B_O * 8, 2048);
                if (!attn) mbar_expect(bar0 + B_F * 8, 256);
            }
            __syncwarp();
            bar_arrive<2, 64>();
        } else if (fw == 1) {
            uint32_t e;
            asm volatile("ld.relaxed.gpu.global.u32 %0, [%1];" : "=r"(e) : "l"(&p.s->epoch) : "memory");
            if (lane == 0) ep_s = e;
        } else if (fw == 2 && !attn) {
            b1_s[lane] = __bfloat162float(p.b1[r * 224 + (cl - 8) * 32 + lane]);
        }
        if (attn) {
            bar_arrive<1, NTHREADS>();
            cluster_arrive();
        } else {
            const int oc = c - 64;
            if (fw == 3 && lane < 8) b1_s[32 + lane] = __bfloat162float(p.x[oc * 8 + lane]) + __bfloat162float(p.b2[oc * 8 + lane]);
            bar_sync<1, NTHREADS>();
            cluster_arrive();
            const uint32_t tag = (ep_s + 1) & 3u;
            uint4 v;
            int it = 0;
            const uint32_t* src = &p.s->fbox[oc][0][0] + t * 4;
            do {
                v = ldg_poll(src);
                if (it == 0) mbar_wait(bar0 + 8 * 8, 0);
            } while (bad4(v, tag) && ++it < SPIN_LIMIT);
            __syncwarp();
            float a[4] = {__uint_as_float(v.x), __uint_as_float(v.y), __uint_as_float(v.z), __uint_as_float(v.w)};
            halve<4, 16>(a, lane); halve<2, 8>(a, lane);
            a[0] += __shfl_xor_sync(0xffffffffu, a[0], 4);
            a[0] += __shfl_xor_sync(0xffffffffu, a[0], 2);
            if (!(lane & 6)) fin_s[(lane & 1) * 4 + (lane >> 4) * 2 + ((lane >> 3) & 1)][fw] = a[0];
            bar_arrive<4, 160>();
        }
    }
}

typedef CUresult (*EncodeFn)(CUtensorMap*, CUtensorMapDataType, cuuint32_t, void*, const cuuint64_t*, const cuuint64_t*,
                             const cuuint32_t*, const cuuint32_t*, CUtensorMapInterleave, CUtensorMapSwizzle,
                             CUtensorMapL2promotion, CUtensorMapFloatOOBfill);

void make_map(EncodeFn encode, CUtensorMap* m, void* base, uint64_t cols, uint64_t rows, uint32_t bc, uint32_t br, bool swz) {
    cuuint64_t gd[2] = {cols, rows}; cuuint64_t gs[1] = {cols * 2}; cuuint32_t bd[2] = {bc, br}; cuuint32_t es[2] = {1, 1};
    encode(m, CU_TENSOR_MAP_DATA_TYPE_BFLOAT16, 2, base, gd, gs, bd, es, CU_TENSOR_MAP_INTERLEAVE_NONE,
           swz ? CU_TENSOR_MAP_SWIZZLE_128B : CU_TENSOR_MAP_SWIZZLE_NONE, CU_TENSOR_MAP_L2_PROMOTION_L2_256B, CU_TENSOR_MAP_FLOAT_OOB_FILL_NONE);
}

}

constexpr uint32_t g_cfg[8] = {5200, 1350, 4700, 0, 13550, 600, 11950, 14000};

extern "C" void kernel_launch(void* const* d_in, const int* in_sizes, int n_in, void* d_out, int out_size) {
    (void)in_sizes; (void)n_in; (void)out_size;
    static EncodeFn encode = nullptr;
    static Scratch* scratch = nullptr;
    if (!encode) {
        void* fn = nullptr;
        cudaDriverEntryPointQueryResult st;
        cudaGetDriverEntryPoint("cuTensorMapEncodeTiled", &fn, cudaEnableDefault, &st);
        encode = (EncodeFn)fn;
        cudaGetSymbolAddress((void**)&scratch, g_scratch);
        cudaFuncSetAttribute(fused_decode_kernel, cudaFuncAttributeMaxDynamicSharedMemorySize, SM_DYN);
    }
    CUtensorMap tq, t1, t2, tv, to;
    make_map(encode, &tq, d_in[3], 4096, D_MODEL, 64, 128, false);
    make_map(encode, &t1, d_in[6], FFN, D_MODEL, 32, 224, false);
    make_map(encode, &t2, d_in[8], D_MODEL, FFN, 64, 32, true);
    make_map(encode, &to, d_in[4], 64, 4096 * 7, 64, 112, true);
    {
        cuuint64_t gd[3] = {64, (cuuint64_t)8 * SK, 4}; cuuint64_t gs[2] = {512, 128}; cuuint32_t bd[3] = {64, 32, 4}; cuuint32_t es[3] = {1, 1, 1};
        CUresult rc = encode(&tv, CU_TENSOR_MAP_DATA_TYPE_BFLOAT16, 3, d_in[2], gd, gs, bd, es, CU_TENSOR_MAP_INTERLEAVE_NONE,
               CU_TENSOR_MAP_SWIZZLE_128B, CU_TENSOR_MAP_L2_PROMOTION_L2_256B, CU_TENSOR_MAP_FLOAT_OOB_FILL_NONE);
        (void)rc;
    }
    Params p;
    p.x = (const __nv_bfloat16*)d_in[0];
    p.k = (const char*)d_in[1];
    p.b1 = (const __nv_bfloat16*)d_in[7];
    p.b2 = (const __nv_bfloat16*)d_in[9];
    p.out = (__nv_bfloat16*)d_out;
    p.s = scratch;
    p.pace = g_cfg[0]; p.t0 = g_cfg[1]; p.pace_wo = g_cfg[2]; p.tw1 = g_cfg[3]; p.tw2 = g_cfg[4]; p.pace_w2 = g_cfg[5]; p.two = g_cfg[6]; p.tpoll = g_cfg[7];
    fused_decode_kernel<<<NCTA, NTHREADS, SM_DYN, cudaStreamPerThread>>>(p, tq, t1, t2, tv, to);
}
```

```cpp
#include <cuda_runtime.h>
#include <cuda_bf16.h>
#include <cuda.h>
#include <stdint.h>

namespace {

constexpr int D_MODEL = 448;
constexpr int FFN = 1792;
constexpr int SK = 65536;
constexpr int WKEYS = 4096;
constexpr int NCTA = 120;
constexpr int TILE = 16384;
constexpr int NS = 12;
constexpr int NTHREADS = 32 * (1 + 8 + 4);
constexpr int SPIN_LIMIT = 1 << 20;
constexpr float LOG2E = 1.4426950408889634f;
#define QSLEEP 150
#define QSLEEP0 500
#define KF 0

constexpr int IT_K = 4, IT_V = 20, NIT = 36;
constexpr int B_FULL = 0, B_EMPTY = NIT, B_Q = NIT + NS, B_ML = B_Q + 1, B_F = B_Q + 2, B_O = B_Q + 3, NBAR = B_O + 8;
constexpr int SM_W2 = 2 * TILE, SM_WO = 4 * TILE;
constexpr int SM_DYN = NS * TILE;

struct Scratch {
    uint32_t qbox[8][512];
    uint32_t hbox[8][256];
    uint32_t sbox[8][8][16];
    uint32_t obox[8][8][8][64];
    uint32_t epoch;
    uint32_t pad[31];
};
__device__ __align__(128) Scratch g_scratch;

struct Params {
    const __nv_bfloat16* x;
    const char* k;
    const __nv_bfloat16* b1;
    const __nv_bfloat16* b2;
    __nv_bfloat16* out;
    Scratch* s;
    uint32_t pace;
    uint32_t t0;
    uint32_t tw1;
    uint32_t two7;
    uint32_t tw2;
    uint32_t pace_w2;
    uint32_t pace_wo;
    uint32_t ip6, ip7;
};

__device__ __forceinline__ uint32_t s2u(const void* p) { return (uint32_t)__cvta_generic_to_shared(p); }
__device__ __forceinline__ void mbar_init(uint32_t b, uint32_t c) { asm volatile("mbarrier.init.shared::cta.b64 [%0], %1;" :: "r"(b), "r"(c) : "memory"); }
__device__ __forceinline__ void mbar_fence_init() { asm volatile("fence.mbarrier_init.release.cluster;" ::: "memory"); }
__device__ __forceinline__ void mbar_expect(uint32_t b, uint32_t bytes) { asm volatile("mbarrier.arrive.expect_tx.shared::cta.b64 _, [%0], %1;" :: "r"(b), "r"(bytes) : "memory"); }
__device__ __forceinline__ void mbar_arrive(uint32_t b, uint32_t n) { asm volatile("mbarrier.arrive.shared::cta.b64 _, [%0], %1;" :: "r"(b), "r"(n) : "memory"); }
__device__ __forceinline__ void mbar_wait(uint32_t b, uint32_t ph) {
    asm volatile("{\n.reg .pred p;\nW: mbarrier.try_wait.parity.shared::cta.b64 p, [%0], %1;\n@p bra D;\nbra W;\nD:\n}" :: "r"(b), "r"(ph) : "memory");
}
__device__ __forceinline__ bool mbar_test(uint32_t b) {
    uint32_t r;
    asm volatile("{\n.reg .pred p;\nmbarrier.test_wait.parity.shared::cta.b64 p, [%1], 0;\nselp.u32 %0, 1, 0, p;\n}" : "=r"(r) : "r"(b) : "memory");
    return r;
}
__device__ __forceinline__ void bulk(uint32_t dst, const void* src, uint32_t bytes, uint32_t bar, uint64_t pol) {
    asm volatile("cp.async.bulk.shared::cluster.global.mbarrier::complete_tx::bytes.L2::cache_hint [%0], [%1], %2, [%3], %4;" :: "r"(dst), "l"(src), "r"(bytes), "r"(bar), "l"(pol) : "memory");
}
__device__ __forceinline__ void tma2d(uint32_t dst, const void* tm, int x, int y, uint32_t bar) {
    asm volatile("cp.async.bulk.tensor.2d.shared::cluster.global.mbarrier::complete_tx::bytes [%0], [%1, {%3, %4}], [%2];" :: "r"(dst), "l"(tm), "r"(bar), "r"(x), "r"(y) : "memory");
}
__device__ __forceinline__ void tma2d_h(uint32_t dst, const void* tm, int x, int y, uint32_t bar, uint64_t pol) {
    asm volatile("cp.async.bulk.tensor.2d.shared::cluster.global.mbarrier::complete_tx::bytes.L2::cache_hint [%0], [%1, {%3, %4}], [%2], %5;" :: "r"(dst), "l"(tm), "r"(bar), "r"(x), "r"(y), "l"(pol) : "memory");
}
__device__ __forceinline__ void tma3d_h(uint32_t dst, const void* tm, int x, int y, int z, uint32_t bar, uint64_t pol) {
    asm volatile("cp.async.bulk.tensor.3d.shared::cluster.global.mbarrier::complete_tx::bytes.L2::cache_hint [%0], [%1, {%3, %4, %5}], [%2], %6;" :: "r"(dst), "l"(tm), "r"(bar), "r"(x), "r"(y), "r"(z), "l"(pol) : "memory");
}
__device__ __forceinline__ uint4 ldsm4t(uint32_t a) { uint4 v; asm volatile("ldmatrix.sync.aligned.m8n8.x4.trans.shared.b16 {%0,%1,%2,%3}, [%4];" : "=r"(v.x), "=r"(v.y), "=r"(v.z), "=r"(v.w) : "r"(a)); return v; }
__device__ __forceinline__ uint32_t mapa(uint32_t a, uint32_t r) { uint32_t d; asm("mapa.shared::cluster.u32 %0, %1, %2;" : "=r"(d) : "r"(a), "r"(r)); return d; }
__device__ __forceinline__ void st_async1(uint32_t a, uint32_t x, uint32_t bar) {
    asm volatile("st.async.weak.shared::cluster.mbarrier::complete_tx::bytes.b32 [%0], %1, [%2];" :: "r"(a), "r"(x), "r"(bar) : "memory");
}
__device__ __forceinline__ void st_async2(uint32_t a, float x, float y, uint32_t bar) {
    asm volatile("st.async.weak.shared::cluster.mbarrier::complete_tx::bytes.v2.f32 [%0], {%1, %2}, [%3];" :: "r"(a), "f"(x), "f"(y), "r"(bar) : "memory");
}
__device__ __forceinline__ void st_async4(uint32_t a, float x, float y, float z, float w, uint32_t bar) {
    asm volatile("st.async.weak.shared::cluster.mbarrier::complete_tx::bytes.v4.f32 [%0], {%1, %2, %3, %4}, [%5];" :: "r"(a), "f"(x), "f"(y), "f"(z), "f"(w), "r"(bar) : "memory");
}
__device__ __forceinline__ void cluster_arrive() { asm volatile("barrier.cluster.arrive.relaxed.aligned;" ::: "memory"); }
__device__ __forceinline__ void cluster_wait() { asm volatile("barrier.cluster.wait.aligned;" ::: "memory"); }
__device__ __forceinline__ bool elect() { uint32_t r; asm volatile("{\n.reg .pred p;\nelect.sync _|p, 0xffffffff;\nselp.u32 %0,1,0,p;\n}" : "=r"(r)); return r; }
__device__ __forceinline__ uint32_t clk() { uint32_t t; asm volatile("mov.u32 %0, %clock;" : "=r"(t) :: "memory"); return t; }
__device__ __forceinline__ uint32_t gtime() { uint32_t t; asm volatile("mov.u32 %0, %globaltimer_lo;" : "=r"(t) :: "memory"); return t; }
template <int ID, int N> __device__ __forceinline__ void bar_sync() { asm volatile("bar.sync %0, %1;" :: "n"(ID), "n"(N) : "memory"); }
template <int ID, int N> __device__ __forceinline__ void bar_arrive() { asm volatile("bar.arrive %0, %1;" :: "n"(ID), "n"(N) : "memory"); }
__device__ __forceinline__ uint4 lds128(uint32_t a) { uint4 v; asm volatile("ld.shared.v4.u32 {%0,%1,%2,%3}, [%4];" : "=r"(v.x), "=r"(v.y), "=r"(v.z), "=r"(v.w) : "r"(a)); return v; }
__device__ __forceinline__ float2 lds64f(uint32_t a) { float2 v; asm volatile("ld.shared.v2.f32 {%0,%1}, [%2];" : "=f"(v.x), "=f"(v.y) : "r"(a)); return v; }
__device__ __forceinline__ uint4 ldg_poll(const void* p) { uint4 v; asm volatile("ld.relaxed.gpu.global.v4.u32 {%0,%1,%2,%3}, [%4];" : "=r"(v.x), "=r"(v.y), "=r"(v.z), "=r"(v.w) : "l"(p) : "memory"); return v; }
__device__ __forceinline__ void stg_pub4(void* p, uint32_t a, uint32_t b, uint32_t c, uint32_t d) { asm volatile("st.relaxed.gpu.global.v4.u32 [%0], {%1,%2,%3,%4};" :: "l"(p), "r"(a), "r"(b), "r"(c), "r"(d) : "memory"); }
__device__ __forceinline__ void stg_pub2(void* p, uint32_t a, uint32_t b) { asm volatile("st.relaxed.gpu.global.v2.u32 [%0], {%1,%2};" :: "l"(p), "r"(a), "r"(b) : "memory"); }
__device__ __forceinline__ void stg_pub1(void* p, uint32_t a) { asm volatile("st.relaxed.gpu.global.u32 [%0], %1;" :: "l"(p), "r"(a) : "memory"); }
__device__ __forceinline__ uint32_t bad4(uint4 v, uint32_t tag) { return ((v.x ^ tag) | (v.y ^ tag) | (v.z ^ tag) | (v.w ^ tag)) & 3u; }
__device__ __forceinline__ uint32_t tagf(float f, uint32_t tag) { return (__float_as_uint(f) & ~3u) | tag; }
__device__ __forceinline__ float bflo(uint32_t u) { return __uint_as_float(u << 16); }
__device__ __forceinline__ float bfhi(uint32_t u) { return __uint_as_float(u & 0xffff0000u); }
__device__ __forceinline__ float rbf(float f) { return __bfloat162float(__float2bfloat16_rn(f)); }
__device__ __forceinline__ uint32_t pack_bf(float lo, float hi) { const __nv_bfloat162 r = __floats2bfloat162_rn(lo, hi); return *reinterpret_cast<const uint32_t*>(&r); }
__device__ __forceinline__ void fma8(float* a, uint4 w, float s) {
    a[0] = fmaf(bflo(w.x), s, a[0]); a[1] = fmaf(bfhi(w.x), s, a[1]);
    a[2] = fmaf(bflo(w.y), s, a[2]); a[3] = fmaf(bfhi(w.y), s, a[3]);
    a[4] = fmaf(bflo(w.z), s, a[4]); a[5] = fmaf(bfhi(w.z), s, a[5]);
    a[6] = fmaf(bflo(w.w), s, a[6]); a[7] = fmaf(bfhi(w.w), s, a[7]);
}
template <int N, int M> __device__ __forceinline__ void halve(float* a, int lane) {
    const bool up = lane & M;
#pragma unroll
    for (int i = 0; i < N / 2; i++) {
        float keep = up ? a[i + N / 2] : a[i];
        float send = up ? a[i] : a[i + N / 2];
        a[i] = keep + __shfl_xor_sync(0xffffffffu, send, M);
    }
}
__device__ __forceinline__ void mma16816(float* c, uint32_t a0, uint32_t a1, uint32_t a2, uint32_t a3, uint32_t b0, uint32_t b1) {
    asm volatile("mma.sync.aligned.m16n8k16.row.col.f32.bf16.bf16.f32 {%0,%1,%2,%3}, {%4,%5,%6,%7}, {%8,%9}, {%0,%1,%2,%3};"
                 : "+f"(c[0]), "+f"(c[1]), "+f"(c[2]), "+f"(c[3]) : "r"(a0), "r"(a1), "r"(a2), "r"(a3), "r"(b0), "r"(b1));
}
#define TLREC(i) do { } while (0)

__global__ void __cluster_dims__(8, 1, 1) __launch_bounds__(NTHREADS, 1)
fused_decode_kernel(const __grid_constant__ Params p, const __grid_constant__ CUtensorMap tq,
                    const __grid_constant__ CUtensorMap t1, const __grid_constant__ CUtensorMap t2,
                    const __grid_constant__ CUtensorMap tv, const __grid_constant__ CUtensorMap to) {
    extern __shared__ __align__(1024) char sm[];
    __shared__ __align__(8) uint64_t bars[NBAR];
    __shared__ __align__(16) float xn_s[D_MODEL];
    __shared__ __align__(16) float red_s[8][64];
    __shared__ __align__(16) uint32_t q_s[8][256];
    __shared__ __align__(16) float2 sc_s[512];
    __shared__ __align__(16) float2 ml_s[8][8];
    __shared__ __align__(16) float in_s[8][8][64];
    __shared__ float b1_s[40];
    __shared__ uint32_t ep_s;

    uint32_t (*p_s)[256] = reinterpret_cast<uint32_t (*)[256]>(red_s);
    uint32_t* h_s = reinterpret_cast<uint32_t*>(sc_s);
    const int c = blockIdx.x;
    const int warp = __shfl_sync(0xffffffffu, threadIdx.x >> 5, 0);
    int lane;
    asm volatile("mov.u32 %0, %laneid;" : "=r"(lane));
    const uint32_t bar0 = s2u(bars), sm0 = s2u(sm);
    const int cl = c >> 3, r = c & 7;
    const bool strm = cl < 8;

    if (warp == 0) {
        uint32_t g0 = 0;
        uint64_t pol;
        asm volatile("createpolicy.fractional.L2::evict_first.b64 %0, 1.0;" : "=l"(pol));
        const int row0 = SK - WKEYS + c * 32;
        if (elect()) {
#pragma unroll
            for (int i = 0; i < 4 + KF; i++) mbar_init(bar0 + (B_FULL + i) * 8, 1);
            mbar_fence_init();
            if (strm) {
#pragma unroll
                for (int i = 0; i < KF; i++) {
                    mbar_expect(bar0 + (IT_K + i) * 8, TILE);
                    bulk(sm0 + (IT_K + i) * TILE, p.k + (size_t)(row0 + (i >> 1) * SK + (i & 1) * 2048) * 512, TILE, bar0 + (IT_K + i) * 8, pol);
                }
#pragma unroll
                for (int i = 0; i < 4; i++) { mbar_expect(bar0 + i * 8, TILE); tma2d(sm0 + i * TILE, &tq, c * 64, i * 128, bar0 + i * 8); }
            }
            g0 = gtime();
            TLREC(19);
        }
        __syncwarp();
        bar_arrive<1, NTHREADS>();
        bar_sync<2, 64>();
        cluster_arrive();
        if (elect()) {
            if (strm) {
                asm volatile("prefetch.tensormap [%0];" :: "l"(&tv) : "memory");
                uint32_t target = p.t0 * 16;
                int slot = IT_K + KF, ph = 1;
#pragma unroll 1
                for (int it = IT_K + KF; it < NIT; it++) {
                    mbar_wait(bar0 + (B_EMPTY + slot) * 8, ph);
                    while ((gtime() - g0) * 16 < target) { }
                    target += p.pace;
                    const uint32_t b = bar0 + (B_FULL + it) * 8, dst = sm0 + slot * TILE;
                    const int tt = (it - IT_K) & 15, row = row0 + (tt >> 1) * SK + (tt & 1) * 2048;
                    mbar_expect(b, TILE);
                    if (it < IT_V) bulk(dst, p.k + (size_t)row * 512, TILE, b, pol);
                    else tma3d_h(dst, &tv, 0, row, 0, b, pol);
                    if (++slot == NS) { slot = 0; ph ^= 1; }
                }
                TLREC(0);
            } else {
                const int k = cl - 8;
                while (gtime() - g0 < p.tw1) { }
                mbar_expect(bar0, 28672);
                tma2d(sm0, &t1, r * 224 + k * 32, 0, bar0);
                tma2d(sm0 + 14336, &t1, r * 224 + k * 32, 224, bar0);
                asm volatile("prefetch.tensormap [%0];" :: "l"(&t2) : "memory");
                while (gtime() - g0 < p.two7) __nanosleep(200);
                mbar_expect(bar0 + 15 * 8, 8192);
                tma2d(sm0 + SM_WO + 7 * 8192, &to, k * 64, 7 * 512 + r * 64, bar0 + 15 * 8);
                while (gtime() - g0 + 600 < p.tw2) __nanosleep(200);
                uint32_t target = p.tw2 * 16;
#pragma unroll 1
                for (int i = 0; i < 14; i++) {
                    while ((gtime() - g0) * 16 < target) { }
                    const uint32_t b = bar0 + (1 + i) * 8;
                    if (i == p.ip6) mbar_arrive(bar0 + 16 * 8, 1);
                    if (i == p.ip7) mbar_arrive(bar0 + 17 * 8, 1);
                    if (i < 7) {
                        target += p.pace_w2;
                        mbar_expect(b, 4096);
                        tma2d(sm0 + SM_W2 + i * 4096, &t2, k * 64, r * 224 + i * 32, b);
                    } else {
                        target += p.pace_wo;
                        mbar_expect(b, 8192);
                        tma2d(sm0 + SM_WO + (i - 7) * 8192, &to, k * 64, (i - 7) * 512 + r * 64, b);
                    }
                }
                TLREC(0);
            }
        }
    } else if (warp <= 8) {
        const int w = warp - 1, t = threadIdx.x - 32;
        const int g = lane >> 2, tq4 = lane & 3;
        {
            const uint32_t* x2 = reinterpret_cast<const uint32_t*>(p.x);
            uint32_t xr[7];
            const uint32_t xm = __ldg(x2 + min(t, 223));
#pragma unroll
            for (int i = 0; i < 7; i++) xr[i] = __ldg(x2 + lane + 32 * i);
            float sum = 0.f;
#pragma unroll
            for (int i = 0; i < 7; i++) sum += bflo(xr[i]) + bfhi(xr[i]);
#pragma unroll
            for (int o = 16; o; o >>= 1) sum += __shfl_xor_sync(0xffffffffu, sum, o);
            const float mean = sum * (1.f / D_MODEL);
            float var = 0.f;
#pragma unroll
            for (int i = 0; i < 7; i++) { float a = bflo(xr[i]) - mean, b = bfhi(xr[i]) - mean; var += a * a + b * b; }
#pragma unroll
            for (int o = 16; o; o >>= 1) var += __shfl_xor_sync(0xffffffffu, var, o);
            const float mb = rbf(mean);
            const float den = rbf(__fsqrt_rn(rbf(rbf(var * (1.f / D_MODEL)) + 1e-5f)));
            if (w < 7) {
                float2 v;
                v.x = rbf(__fdiv_rn(rbf(bflo(xm) - mb), den));
                v.y = rbf(__fdiv_rn(rbf(bfhi(xm) - mb), den));
                *reinterpret_cast<float2*>(&xn_s[2 * t]) = v;
            }
        }
        bar_sync<1, NTHREADS>();
        cluster_arrive();
        const uint32_t tag = (ep_s + 1) & 3u;
        if (t == 0) TLREC(1);

        if (strm) {
            if (w == 0) stg_pub2(&p.s->qbox[cl][r * 64 + 2 * lane], tag ^ 2u, tag ^ 2u);
            {
                float a[8];
#pragma unroll
                for (int i = 0; i < 8; i++) a[i] = 0.f;
#pragma unroll 1
                for (int b = 0; b < 4; b++) {
                    mbar_wait(bar0 + (B_FULL + b) * 8, 0);
                    const uint32_t base = sm0 + b * TILE + t * 16;
                    const float* xs = &xn_s[b * 128 + (t >> 3)];
                    fma8(a, lds128(base), xs[0]);
                    fma8(a, lds128(base + 4096), xs[32]);
                    if (b < 3) {
                        fma8(a, lds128(base + 8192), xs[64]);
                        fma8(a, lds128(base + 12288), xs[96]);
                    }
                    __syncwarp();
                    if (lane == 0) mbar_arrive(bar0 + (B_EMPTY + b) * 8, 1);
                }
                if (t == 0) TLREC(18);
                halve<8, 16>(a, lane); halve<4, 8>(a, lane);
                *reinterpret_cast<float2*>(&red_s[w][(lane & 7) * 8 + (lane >> 3) * 2]) = make_float2(a[0], a[1]);
                bar_sync<3, 256>();
                if (w == 0) {
                    float q0 = 0.f, q1 = 0.f;
#pragma unroll
                    for (int i = 0; i < 8; i++) { const float2 v = *reinterpret_cast<const float2*>(&red_s[i][2 * lane]); q0 += v.x; q1 += v.y; }
                    stg_pub2(&p.s->qbox[cl][r * 64 + 2 * lane], __float_as_uint(rbf(q0)) | tag, __float_as_uint(rbf(q1)) | tag);
                    if (t == 0) TLREC(2);
                }
            }
            mbar_wait(bar0 + B_Q * 8, 0);
            if (t == 0) TLREC(3);
#pragma unroll 1
            for (int i4 = 0; i4 < 4; i4++) {
                const int tile = (w >> 1) + 4 * i4, it = IT_K + tile;
                const int slot = it >= NS ? it - NS : it;
                uint4 qf[8];
#pragma unroll
                for (int i = 0; i < 8; i++) {
                    qf[i] = make_uint4(0, 0, 0, 0);
                    if (g < 2) qf[i] = lds128(s2u(&q_s[tile >> 1][0]) + g * 512 + i * 64 + tq4 * 16);
                }
                mbar_wait(bar0 + (B_FULL + it) * 8, 0);
                float ca[4] = {0.f, 0.f, 0.f, 0.f}, cb[4] = {0.f, 0.f, 0.f, 0.f};
                const uint32_t base = sm0 + slot * TILE + (w & 1) * 8192 + g * 512 + tq4 * 16;
#pragma unroll
                for (int i = 0; i < 8; i++) {
                    const uint4 lo = lds128(base + i * 64), hi = lds128(base + 4096 + i * 64);
                    mma16816(ca, lo.x, hi.x, lo.y, hi.y, qf[i].x, qf[i].y);
                    mma16816(cb, lo.z, hi.z, lo.w, hi.w, qf[i].z, qf[i].w);
                }
                if (lane == 0) mbar_arrive(bar0 + (B_EMPTY + slot) * 8, 4);
                if (tq4 == 0) {
                    const int key = tile * 32 + (w & 1) * 16 + g;
                    sc_s[key] = make_float2(rbf(ca[0] + cb[0]) * 0.0625f, rbf(ca[1] + cb[1]) * 0.0625f);
                    sc_s[key + 8] = make_float2(rbf(ca[2] + cb[2]) * 0.0625f, rbf(ca[3] + cb[3]) * 0.0625f);
                }
            }
            bar_sync<3, 256>();
            {
                if (t == 0) TLREC(4);
                float4 s = *reinterpret_cast<const float4*>(&sc_s[2 * t]);
                float m0 = fmaxf(s.x, s.z), m1 = fmaxf(s.y, s.w);
#pragma unroll
                for (int o = 16; o; o >>= 1) { m0 = fmaxf(m0, __shfl_xor_sync(0xffffffffu, m0, o)); m1 = fmaxf(m1, __shfl_xor_sync(0xffffffffu, m1, o)); }
                s.x = exp2f((s.x - m0) * LOG2E); s.y = exp2f((s.y - m1) * LOG2E);
                s.z = exp2f((s.z - m0) * LOG2E); s.w = exp2f((s.w - m1) * LOG2E);
                const int pos = (t & ~15) + (t & 3) * 4 + ((t >> 2) & 3);
                p_s[0][pos] = pack_bf(s.x, s.z);
                p_s[1][pos] = pack_bf(s.y, s.w);
                float l0 = s.x + s.z, l1 = s.y + s.w;
#pragma unroll
                for (int o = 16; o; o >>= 1) { l0 += __shfl_xor_sync(0xffffffffu, l0, o); l1 += __shfl_xor_sync(0xffffffffu, l1, o); }
                cluster_wait();
                if (lane < 8) st_async2(mapa(s2u(&ml_s[w][r]), lane), lane < 4 ? m0 : m1, lane < 4 ? l0 : l1, mapa(bar0 + B_ML * 8, lane));
                bar_sync<3, 256>();
            }
            {
                const uint32_t lo = sm0 + (w >> 1) * 4096 + ((lane & 7) + 8 * (lane >> 4)) * 128;
                const uint32_t sw = ((w & 1) * 4 + ((lane >> 3) & 1)) ^ (lane & 7);
                const uint32_t pa = s2u(&p_s[g & 1][tq4 * 4]);
                const int dst = (tq4 & 1) * 4 + (w >> 1);
                const uint32_t da = mapa(s2u(&in_s[0][r][(w & 1) * 32 + (tq4 >> 1) * 16 + g]), dst), db = mapa(bar0 + B_O * 8, dst);
                int slot = IT_V - NS;
#pragma unroll 1
                for (int h = 0; h < 8; h++) {
                    float acc[4][4];
#pragma unroll
                    for (int i = 0; i < 4; i++) { acc[i][0] = acc[i][1] = acc[i][2] = acc[i][3] = 0.f; }
#pragma unroll
                    for (int j = 0; j < 2; j++) {
                        const uint4 pf = lds128(pa + (2 * h + j) * 64);
                        const uint32_t base = lo + (slot + j) * TILE;
                        mbar_wait(bar0 + (B_FULL + IT_V + 2 * h + j) * 8, 0);
                        uint4 vf[4];
#pragma unroll
                        for (int i = 0; i < 4; i++) vf[i] = ldsm4t(base + (i >> 1) * 2048 + ((sw ^ (2 * (i & 1))) << 4));
                        mma16816(acc[0], vf[0].x, vf[0].y, vf[0].z, vf[0].w, pf.x, pf.y);
                        mma16816(acc[1], vf[1].x, vf[1].y, vf[1].z, vf[1].w, pf.x, pf.y);
                        mma16816(acc[2], vf[2].x, vf[2].y, vf[2].z, vf[2].w, pf.z, pf.w);
                        mma16816(acc[3], vf[3].x, vf[3].y, vf[3].z, vf[3].w, pf.z, pf.w);
                        if (lane == 0) mbar_arrive(bar0 + (B_EMPTY + slot + j) * 8, 1);
                    }
                    slot += 2;
                    if (slot == NS) slot = 0;
                    const bool hi = tq4 & 2, h1 = tq4 & 1;
                    const float x0 = hi ? acc[1][0] + acc[3][0] : acc[0][0] + acc[2][0], x1 = hi ? acc[1][1] + acc[3][1] : acc[0][1] + acc[2][1];
                    const float x2 = hi ? acc[1][2] + acc[3][2] : acc[0][2] + acc[2][2], x3 = hi ? acc[1][3] + acc[3][3] : acc[0][3] + acc[2][3];
                    st_async1(da + h * 2048, __float_as_uint(h1 ? x1 : x0), db + h * 8);
                    st_async1(da + h * 2048 + 32, __float_as_uint(h1 ? x3 : x2), db + h * 8);
                }
                if (t == 0) TLREC(6);
            }
        } else {
            const int k = cl - 8;
            if (w == 0) stg_pub1(&p.s->hbox[r][k * 32 + lane], tag ^ 2u);
            {
                float a[8];
#pragma unroll
                for (int i = 0; i < 8; i++) a[i] = 0.f;
                mbar_wait(bar0, 0);
#pragma unroll 1
                for (int i = 0; i < 7; i++) fma8(a, lds128(sm0 + (t + 256 * i) * 16), xn_s[(t >> 2) + 64 * i]);
                halve<8, 16>(a, lane); halve<4, 8>(a, lane); halve<2, 4>(a, lane);
                red_s[w][(lane & 3) * 8 + (lane >> 2)] = a[0];
                bar_sync<3, 256>();
                if (w == 0) {
                    float h = 0.f;
#pragma unroll
                    for (int i = 0; i < 8; i++) h += red_s[i][lane];
                    h = rbf(rbf(h) + b1_s[lane]);
                    const float u = 0.7978845608028654f * (h + 0.044715f * h * h * h);
                    stg_pub1(&p.s->hbox[r][k * 32 + lane], __float_as_uint(rbf(0.5f * h * (1.f + tanhf(u)))) | tag);
                    if (t == 0) TLREC(2);
                }
                if (t < 56) {
                    uint4 v;
                    int it = 0;
                    do { __nanosleep(1000); v = ldg_poll(&p.s->hbox[r][t * 4]); } while (bad4(v, tag) && ++it < SPIN_LIMIT);
                    const int pi = 2 * t, pos = (pi & ~15) + (pi & 3) * 4 + ((pi >> 2) & 3);
                    h_s[pos] = __byte_perm(v.x, v.y, 0x7632);
                    h_s[pos + 4] = __byte_perm(v.z, v.w, 0x7632);
                }
                bar_sync<3, 256>();
                if (t == 0) TLREC(3);
            }
            cluster_wait();
            {
                float acc[4] = {0.f, 0.f, 0.f, 0.f};
                const uint32_t base = sm0 + SM_W2 + ((lane & 7) + 16 * ((lane >> 3) & 1) + 8 * (lane >> 4)) * 128 + ((w ^ (lane & 7)) << 4);
#pragma unroll 1
                for (int i = 0; i < 7; i++) {
                    const uint2 hf = *reinterpret_cast<const uint2*>(&h_s[i * 16 + tq4 * 4 + (g & 1) * 2]);
                    mbar_wait(bar0 + (1 + i) * 8, 0);
                    const uint4 u = ldsm4t(base + i * 4096);
                    mma16816(acc, u.x, u.y, u.z, u.w, hf.x, hf.y);
                }
                if (tq4 == 0) st_async1(mapa(s2u(&in_s[0][0][(48 + r) * 8 + g]), w), __float_as_uint(acc[0] + acc[3]), mapa(bar0 + B_F * 8, w));
            }
            if (t == 0) TLREC(5);
            {
                float acc[2][4] = {{0.f, 0.f, 0.f, 0.f}, {0.f, 0.f, 0.f, 0.f}};
                const uint32_t base = sm0 + SM_WO + (w >> 2) * 4096 + ((lane & 7) + 8 * (lane >> 4)) * 128 + (((2 * (w & 3) + ((lane >> 3) & 1)) ^ (lane & 7)) << 4);
                const uint32_t ba = s2u(&q_s[0][(w >> 2) * 128 + lane * 4]);
                const int dst = 2 * (w & 3) + (tq4 & 1);
                const uint32_t da = mapa(s2u(&in_s[0][0][(32 + 2 * r + (w >> 2)) * 8 + g]), dst), db = mapa(bar0 + B_F * 8, dst);
                uint4 bf[7], u0[7], u1[7];
#pragma unroll
                for (int h = 0; h < 7; h++) {
                    if (h == 3) {
                        mbar_wait(bar0 + B_EMPTY * 8, 0);
#pragma unroll
                        for (int i = 0; i < 6; i++) bf[i] = lds128(ba + i * 1024);
                    }
                    if (h == 6) { mbar_wait(bar0 + (B_EMPTY + 1) * 8, 0); bf[6] = lds128(ba + 6 * 1024); }
                    mbar_wait(bar0 + (8 + h) * 8, 0);
                    u0[h] = ldsm4t(base + h * 8192); u1[h] = ldsm4t(base + h * 8192 + 2048);
#pragma unroll
                    for (int i = (h <= 3 ? 0 : h - 1); i < (h < 3 ? 0 : h == 6 ? 7 : h); i++) {
                        mma16816(acc[0], u0[i].x, u0[i].y, u0[i].z, u0[i].w, bf[i].x, bf[i].y);
                        mma16816(acc[1], u1[i].x, u1[i].y, u1[i].z, u1[i].w, bf[i].z, bf[i].w);
                    }
                }
                float a[2] = {(acc[0][0] + acc[0][1]) + (acc[1][0] + acc[1][1]), (acc[0][2] + acc[0][3]) + (acc[1][2] + acc[1][3])};
                halve<2, 1>(a, lane);
                a[0] += __shfl_xor_sync(0xffffffffu, a[0], 2);
                if (tq4 < 2) st_async1(da, __float_as_uint(a[0]), db);
                if (t == 0) TLREC(8);
            }
        }
    } else {
        const int fw = warp - 9, t = threadIdx.x - 288;
        if (fw == 0) {
            if (elect()) {
#pragma unroll
                for (int i = 4 + KF; i < NBAR; i++) mbar_init(bar0 + i * 8, (i >= B_EMPTY && i < B_Q) ? 8 : 1);
                mbar_fence_init();
            }
            __syncwarp();
            bar_arrive<2, 64>();
            if (elect()) {
                mbar_expect(bar0 + B_Q * 8, 8192);
                mbar_expect(bar0 + B_ML * 8, 512);
                mbar_expect(bar0 + B_F * 8, 56 * 32);
#pragma unroll
                for (int i = 0; i < 8; i++) mbar_expect(bar0 + (B_O + i) * 8, 2048);
            }
            __syncwarp();
        } else if (fw == 1) {
            uint32_t e;
            asm volatile("ld.relaxed.gpu.global.u32 %0, [%1];" : "=r"(e) : "l"(&p.s->epoch) : "memory");
            if (lane == 0) ep_s = e;
        } else if (!strm) {
            if (fw == 2) {
                b1_s[lane] = __bfloat162float(p.b1[r * 224 + (cl - 8) * 32 + lane]);
            } else {
                const int col = (c - 64) * 8 + (lane & 7);
                if (lane < 8) b1_s[32 + lane] = __bfloat162float(p.x[col]) + __bfloat162float(p.b2[col]);
            }
        }
        bar_sync<1, NTHREADS>();
        cluster_arrive();
        const uint32_t tag = (ep_s + 1) & 3u;
        if (strm) {
            {
                uint4 v;
                int it = 0;
                mbar_wait(bar0 + (B_EMPTY + 3) * 8, 0);
                while (true) {
                    __nanosleep(it ? QSLEEP : QSLEEP0);
                    v = ldg_poll(&p.s->qbox[r][t * 4]);
                    if (!bad4(v, tag) || ++it >= SPIN_LIMIT) break;
                }
                __syncwarp();
                cluster_wait();
                const float lo = __uint_as_float(__byte_perm(v.x, v.y, 0x7632)), hi = __uint_as_float(__byte_perm(v.z, v.w, 0x7632));
#pragma unroll
                for (int d = 0; d < 8; d++) st_async2(mapa(s2u(&q_s[r][t * 2]), d), lo, hi, mapa(bar0 + B_Q * 8, d));
            }
            if (fw == 0) {
                uint32_t* dst = &p.s->obox[0][r][cl][(lane & 3) * 16 + (lane >> 2) * 2];
#pragma unroll
                for (int h = 0; h < 8; h++) stg_pub2(dst + h * 4096, tag ^ 2u, tag ^ 2u);
                if ((lane & 7) == 0) { stg_pub2(&p.s->sbox[r][cl][2 * (lane >> 3)], tag ^ 2u, tag ^ 2u); stg_pub2(&p.s->sbox[r][cl][2 * (lane >> 3) + 8], tag ^ 2u, tag ^ 2u); }
                mbar_wait(bar0 + B_ML * 8, 0);
                float e[2];
#pragma unroll
                for (int i = 0; i < 2; i++) {
                    const float2 v = ml_s[(lane >> 3) + 4 * i][lane & 7];
                    float M = v.x;
#pragma unroll
                    for (int o = 1; o < 8; o <<= 1) M = fmaxf(M, __shfl_xor_sync(0xffffffffu, M, o));
                    e[i] = exp2f((v.x - M) * LOG2E);
                    float L = v.y * e[i];
#pragma unroll
                    for (int o = 1; o < 8; o <<= 1) L += __shfl_xor_sync(0xffffffffu, L, o);
                    if ((lane & 7) == 0) stg_pub2(&p.s->sbox[r][cl][2 * ((lane >> 3) + 4 * i)], tagf(M, tag), tagf(L, tag));
                }
#pragma unroll 1
                for (int h = 0; h < 8; h++) {
                    float ws[8];
#pragma unroll
                    for (int s = 0; s < 8; s++) ws[s] = __shfl_sync(0xffffffffu, h < 4 ? e[0] : e[1], (h & 3) * 8 + s);
                    mbar_wait(bar0 + (B_O + h) * 8, 0);
                    float2 ov[8];
#pragma unroll
                    for (int s = 0; s < 8; s++) ov[s] = lds64f(s2u(&in_s[h][s][2 * lane]));
                    const float o0 = (fmaf(ov[0].x, ws[0], ov[1].x * ws[1]) + fmaf(ov[2].x, ws[2], ov[3].x * ws[3])) + (fmaf(ov[4].x, ws[4], ov[5].x * ws[5]) + fmaf(ov[6].x, ws[6], ov[7].x * ws[7]));
                    const float o1 = (fmaf(ov[0].y, ws[0], ov[1].y * ws[1]) + fmaf(ov[2].y, ws[2], ov[3].y * ws[3])) + (fmaf(ov[4].y, ws[4], ov[5].y * ws[5]) + fmaf(ov[6].y, ws[6], ov[7].y * ws[7]));
                    stg_pub2(dst + h * 4096, tagf(o0, tag), tagf(o1, tag));
                }
                if (lane == 0) TLREC(9);
            }
        } else {
            const int g = lane >> 2, tq4 = lane & 3;
            mbar_wait(bar0 + 15 * 8, 0);
            uint4 wf[4];
#pragma unroll
            for (int j = 0; j < 4; j++)
                wf[j] = ldsm4t(sm0 + SM_WO + 7 * 8192 + fw * 2048 + ((lane & 7) + 8 * (lane >> 4)) * 128 + (((2 * j + ((lane >> 3) & 1)) ^ (lane & 7)) << 4));
            float wgt[2];
            {
                uint4 v;
                int it = 0;
                while (true) {
                    v = ldg_poll(&p.s->sbox[r][g][4 * tq4]);
                    if (!__any_sync(0xffffffffu, bad4(v, tag)) || ++it >= SPIN_LIMIT) break;
                    __nanosleep(300);
                }
#pragma unroll
                for (int i = 0; i < 2; i++) {
                    const float m = __uint_as_float((i ? v.z : v.x) & ~3u);
                    float M = m;
#pragma unroll
                    for (int o = 4; o < 32; o <<= 1) M = fmaxf(M, __shfl_xor_sync(0xffffffffu, M, o));
                    const float e = exp2f((m - M) * LOG2E);
                    float L = __uint_as_float((i ? v.w : v.y) & ~3u) * e;
#pragma unroll
                    for (int o = 4; o < 32; o <<= 1) L += __shfl_xor_sync(0xffffffffu, L, o);
                    wgt[i] = __fdividef(e, L);
                }
                if (t == 0) TLREC(4);
            }
            const uint32_t fa = s2u(&in_s[0][0][(r * 4 + fw) * 8 + g]);
            const uint32_t da0 = mapa(fa, 2 * tq4), db0 = mapa(bar0 + B_F * 8, 2 * tq4), da1 = mapa(fa, 2 * tq4 + 1), db1 = mapa(bar0 + B_F * 8, 2 * tq4 + 1);
            cluster_wait();
            const uint32_t* src = &p.s->obox[0][r][g][tq4 * 16 + fw * 4];
            uint2* bdst = reinterpret_cast<uint2*>(&q_s[0][(fw >> 1) * 128 + lane * 4 + (fw & 1) * 2]);
            auto frag = [&](uint4 v, int h) {
                const float wg = __shfl_sync(0xffffffffu, wgt[h & 1], (lane & 28) + (h >> 1));
                return make_uint2(pack_bf(__uint_as_float(v.x) * wg, __uint_as_float(v.y) * wg), pack_bf(__uint_as_float(v.z) * wg, __uint_as_float(v.w) * wg));
            };
            {
                uint4 ov[6];
                int it = 0;
                mbar_wait(bar0 + 16 * 8, 0);
                while (true) {
#pragma unroll
                    for (int h = 0; h < 6; h++) ov[h] = ldg_poll(src + h * 4096);
                    const uint32_t bad = (bad4(ov[5], tag) | bad4(ov[4], tag) | bad4(ov[3], tag)) | (bad4(ov[2], tag) | bad4(ov[1], tag) | bad4(ov[0], tag));
                    if (!__any_sync(0xffffffffu, bad) || ++it >= SPIN_LIMIT) break;
                    __nanosleep(100);
                }
#pragma unroll
                for (int h = 0; h < 6; h++) bdst[h * 128] = frag(ov[h], h);
                __syncwarp();
                if (lane == 0) mbar_arrive(bar0 + B_EMPTY * 8, 2);
                if (t == 0) TLREC(10);
            }
            const float wg7 = __shfl_sync(0xffffffffu, wgt[1], (lane & 28) + 3);
            uint4 ov;
            {
                int it = 0;
                mbar_wait(bar0 + 17 * 8, 0);
                while (true) {
                    const uint4 v = ldg_poll(src + 6 * 4096);
                    ov = ldg_poll(src + 7 * 4096);
                    if (!__any_sync(0xffffffffu, bad4(v, tag)) || ++it >= SPIN_LIMIT) {
                        bdst[6 * 128] = frag(v, 6);
                        __syncwarp();
                        if (lane == 0) mbar_arrive(bar0 + (B_EMPTY + 1) * 8, 2);
                        break;
                    }
                }
                if (t == 0) TLREC(12);
                while (__any_sync(0xffffffffu, bad4(ov, tag)) && ++it < SPIN_LIMIT) ov = ldg_poll(src + 7 * 4096);
            }
            if (t == 0) TLREC(7);
            const uint32_t b0 = pack_bf(__uint_as_float(ov.x) * wg7, __uint_as_float(ov.y) * wg7), b1 = pack_bf(__uint_as_float(ov.z) * wg7, __uint_as_float(ov.w) * wg7);
            float a[8];
#pragma unroll
            for (int j = 0; j < 4; j++) {
                float acc[4] = {0.f, 0.f, 0.f, 0.f};
                mma16816(acc, wf[j].x, wf[j].y, wf[j].z, wf[j].w, b0, b1);
                a[2 * j] = acc[0] + acc[1]; a[2 * j + 1] = acc[2] + acc[3];
            }
            halve<8, 2>(a, lane); halve<4, 1>(a, lane);
            st_async1(da0, __float_as_uint(a[0]), db0);
            st_async1(da1, __float_as_uint(a[1]), db1);
            if (t == 0) TLREC(9);
            if (fw == 0) {
                const float base = b1_s[32 + (lane & 7)];
                __nv_bfloat16* dst = p.out + (c - 64) * 8 + (lane & 7);
                mbar_wait(bar0 + B_F * 8, 0);
                float s[14];
#pragma unroll
                for (int i = 0; i < 14; i++) s[i] = *reinterpret_cast<const volatile float*>(&in_s[0][0][i * 32 + lane]);
                float v = (((s[0] + s[1]) + (s[2] + s[3])) + ((s[4] + s[5]) + (s[6] + s[7]))) + (((s[8] + s[9]) + (s[10] + s[11])) + (s[12] + s[13]));
                v += __shfl_xor_sync(0xffffffffu, v, 8);
                v += __shfl_xor_sync(0xffffffffu, v, 16);
                if (lane < 8) *dst = __float2bfloat16_rn(v + base);
                if (c == 64 && lane == 0) p.s->epoch = ep_s + 1;
                if (lane == 0) TLREC(11);
            }
        }
    }
}

typedef CUresult (*EncodeFn)(CUtensorMap*, CUtensorMapDataType, cuuint32_t, void*, const cuuint64_t*, const cuuint64_t*,
                             const cuuint32_t*, const cuuint32_t*, CUtensorMapInterleave, CUtensorMapSwizzle,
                             CUtensorMapL2promotion, CUtensorMapFloatOOBfill);

void make_map(EncodeFn encode, CUtensorMap* m, void* base, uint64_t cols, uint64_t rows, uint32_t bc, uint32_t br, bool swz) {
    cuuint64_t gd[2] = {cols, rows}; cuuint64_t gs[1] = {cols * 2}; cuuint32_t bd[2] = {bc, br}; cuuint32_t es[2] = {1, 1};
    encode(m, CU_TENSOR_MAP_DATA_TYPE_BFLOAT16, 2, base, gd, gs, bd, es, CU_TENSOR_MAP_INTERLEAVE_NONE,
           swz ? CU_TENSOR_MAP_SWIZZLE_128B : CU_TENSOR_MAP_SWIZZLE_NONE, CU_TENSOR_MAP_L2_PROMOTION_L2_256B, CU_TENSOR_MAP_FLOAT_OOB_FILL_NONE);
}

}

constexpr uint32_t g_cfg[9] = {5250, 1200, 700, 9200, 11700, 1150, 2300, 7, 12};

extern "C" void kernel_launch(void* const* d_in, const int* in_sizes, int n_in, void* d_out, int out_size) {
    (void)in_sizes; (void)n_in; (void)out_size;
    static EncodeFn encode = nullptr;
    static Scratch* scratch = nullptr;
    if (!encode) {
        void* fn = nullptr;
        cudaDriverEntryPointQueryResult st;
        cudaGetDriverEntryPoint("cuTensorMapEncodeTiled", &fn, cudaEnableDefault, &st);
        encode = (EncodeFn)fn;
        cudaGetSymbolAddress((void**)&scratch, g_scratch);
        cudaFuncSetAttribute(fused_decode_kernel, cudaFuncAttributeMaxDynamicSharedMemorySize, SM_DYN);
    }
    CUtensorMap tq, t1, t2, tv, to;
    make_map(encode, &tq, d_in[3], 4096, D_MODEL, 64, 128, false);
    make_map(encode, &t1, d_in[6], FFN, D_MODEL, 32, 224, false);
    make_map(encode, &t2, d_in[8], D_MODEL, FFN, 64, 32, true);
    make_map(encode, &to, d_in[4], D_MODEL, 4096, 64, 64, true);
    {
        cuuint64_t gd[3] = {64, (cuuint64_t)8 * SK, 4}; cuuint64_t gs[2] = {512, 128}; cuuint32_t bd[3] = {64, 32, 4}; cuuint32_t es[3] = {1, 1, 1};
        CUresult rc = encode(&tv, CU_TENSOR_MAP_DATA_TYPE_BFLOAT16, 3, d_in[2], gd, gs, bd, es, CU_TENSOR_MAP_INTERLEAVE_NONE,
               CU_TENSOR_MAP_SWIZZLE_128B, CU_TENSOR_MAP_L2_PROMOTION_L2_256B, CU_TENSOR_MAP_FLOAT_OOB_FILL_NONE);
        (void)rc;
    }
    Params p;
    p.x = (const __nv_bfloat16*)d_in[0];
    p.k = (const char*)d_in[1];
    p.b1 = (const __nv_bfloat16*)d_in[7];
    p.b2 = (const __nv_bfloat16*)d_in[9];
    p.out = (__nv_bfloat16*)d_out;
    p.s = scratch;
    p.pace = g_cfg[0]; p.t0 = g_cfg[1]; p.tw1 = g_cfg[2]; p.two7 = g_cfg[3]; p.tw2 = g_cfg[4]; p.pace_w2 = g_cfg[5]; p.pace_wo = g_cfg[6]; p.ip6 = g_cfg[7]; p.ip7 = g_cfg[8];
    fused_decode_kernel<<<NCTA, NTHREADS, SM_DYN, cudaStreamPerThread>>>(p, tq, t1, t2, tv, to);
}
```

```cpp
#include <cuda_runtime.h>
#include <cuda_bf16.h>
#include <cuda.h>
#include <stdint.h>

namespace {

constexpr int D_MODEL = 448;
constexpr int FFN = 1792;
constexpr int SK = 65536;
constexpr int WKEYS = 4096;
constexpr int NCTA = 120;
constexpr int TILE = 16384;
constexpr int NS = 12;
constexpr int NTHREADS = 32 * (1 + 8 + 5);
constexpr int SPIN_LIMIT = 1 << 20;
constexpr float LOG2E = 1.4426950408889634f;
#define QSLEEP 150
#define QSLEEP0 500
#define V4D 1
#define VPROM 0
#define WPROM 2
#define W2C 1
#define WHINT 0
#define EARLY 1
#define DEDUP 1
#define KF 1

constexpr int IT_K = 4, IT_V = 20, NIT = 36;
constexpr int B_FULL = 0, B_EMPTY = NIT, B_Q = NIT + NS, B_ML = B_Q + 1, B_F = B_Q + 2, B_O = B_Q + 3, NBAR = B_O + 8;
constexpr int SM_W2 = 2 * TILE, SM_WO = 4 * TILE;
constexpr int SM_DYN = NS * TILE;

struct Scratch {
    uint32_t qbox[8][512];
    uint32_t hbox[8][256];
    uint32_t sbox[8][8][16];
    uint32_t obox[8][8][8][64];
    uint32_t epoch;
    uint32_t pad[31];
};
__device__ __align__(128) Scratch g_scratch;

struct Params {
    const __nv_bfloat16* x;
    const char* k;
    const __nv_bfloat16* b1;
    const __nv_bfloat16* b2;
    __nv_bfloat16* out;
    Scratch* s;
    uint32_t pace;
    uint32_t t0;
    uint32_t tw1;
    uint32_t two7;
    uint32_t tw2;
    uint32_t pace_w2;
    uint32_t pace_wo;
    uint32_t to6, to7;
};

__device__ __forceinline__ uint32_t s2u(const void* p) { return (uint32_t)__cvta_generic_to_shared(p); }
__device__ __forceinline__ void mbar_init(uint32_t b, uint32_t c) { asm volatile("mbarrier.init.shared::cta.b64 [%0], %1;" :: "r"(b), "r"(c) : "memory"); }
__device__ __forceinline__ void mbar_fence_init() { asm volatile("fence.mbarrier_init.release.cluster;" ::: "memory"); }
__device__ __forceinline__ void mbar_expect(uint32_t b, uint32_t bytes) { asm volatile("mbarrier.arrive.expect_tx.shared::cta.b64 _, [%0], %1;" :: "r"(b), "r"(bytes) : "memory"); }
__device__ __forceinline__ void mbar_arrive(uint32_t b, uint32_t n) { asm volatile("mbarrier.arrive.shared::cta.b64 _, [%0], %1;" :: "r"(b), "r"(n) : "memory"); }
__device__ __forceinline__ void mbar_wait(uint32_t b, uint32_t ph) {
    asm volatile("{\n.reg .pred p;\nW: mbarrier.try_wait.parity.shared::cta.b64 p, [%0], %1;\n@p bra D;\nbra W;\nD:\n}" :: "r"(b), "r"(ph) : "memory");
}
__device__ __forceinline__ bool mbar_test(uint32_t b) {
    uint32_t r;
    asm volatile("{\n.reg .pred p;\nmbarrier.test_wait.parity.shared::cta.b64 p, [%1], 0;\nselp.u32 %0, 1, 0, p;\n}" : "=r"(r) : "r"(b) : "memory");
    return r;
}
__device__ __forceinline__ void bulk(uint32_t dst, const void* src, uint32_t bytes, uint32_t bar, uint64_t pol) {
    asm volatile("cp.async.bulk.shared::cluster.global.mbarrier::complete_tx::bytes.L2::cache_hint [%0], [%1], %2, [%3], %4;" :: "r"(dst), "l"(src), "r"(bytes), "r"(bar), "l"(pol) : "memory");
}
__device__ __forceinline__ void tma2d(uint32_t dst, const void* tm, int x, int y, uint32_t bar) {
    asm volatile("cp.async.bulk.tensor.2d.shared::cluster.global.mbarrier::complete_tx::bytes [%0], [%1, {%3, %4}], [%2];" :: "r"(dst), "l"(tm), "r"(bar), "r"(x), "r"(y) : "memory");
}
__device__ __forceinline__ void tma2d_h(uint32_t dst, const void* tm, int x, int y, uint32_t bar, uint64_t pol) {
    asm volatile("cp.async.bulk.tensor.2d.shared::cluster.global.mbarrier::complete_tx::bytes.L2::cache_hint [%0], [%1, {%3, %4}], [%2], %5;" :: "r"(dst), "l"(tm), "r"(bar), "r"(x), "r"(y), "l"(pol) : "memory");
}
__device__ __forceinline__ void tma3d_h(uint32_t dst, const void* tm, int x, int y, int z, uint32_t bar, uint64_t pol) {
    asm volatile("cp.async.bulk.tensor.3d.shared::cluster.global.mbarrier::complete_tx::bytes.L2::cache_hint [%0], [%1, {%3, %4, %5}], [%2], %6;" :: "r"(dst), "l"(tm), "r"(bar), "r"(x), "r"(y), "r"(z), "l"(pol) : "memory");
}
__device__ __forceinline__ void tma4d_h(uint32_t dst, const void* tm, int y, uint32_t bar, uint64_t pol) {
    asm volatile("cp.async.bulk.tensor.4d.shared::cluster.global.mbarrier::complete_tx::bytes.L2::cache_hint [%0], [%1, {0, 0, 0, %3}], [%2], %4;" :: "r"(dst), "l"(tm), "r"(bar), "r"(y), "l"(pol) : "memory");
}
__device__ __forceinline__ uint4 ldsm4t(uint32_t a) { uint4 v; asm volatile("ldmatrix.sync.aligned.m8n8.x4.trans.shared.b16 {%0,%1,%2,%3}, [%4];" : "=r"(v.x), "=r"(v.y), "=r"(v.z), "=r"(v.w) : "r"(a)); return v; }
__device__ __forceinline__ uint32_t mapa(uint32_t a, uint32_t r) { uint32_t d; asm("mapa.shared::cluster.u32 %0, %1, %2;" : "=r"(d) : "r"(a), "r"(r)); return d; }
__device__ __forceinline__ void st_async1(uint32_t a, uint32_t x, uint32_t bar) {
    asm volatile("st.async.weak.shared::cluster.mbarrier::complete_tx::bytes.b32 [%0], %1, [%2];" :: "r"(a), "r"(x), "r"(bar) : "memory");
}
__device__ __forceinline__ void st_async2(uint32_t a, float x, float y, uint32_t bar) {
    asm volatile("st.async.weak.shared::cluster.mbarrier::complete_tx::bytes.v2.f32 [%0], {%1, %2}, [%3];" :: "r"(a), "f"(x), "f"(y), "r"(bar) : "memory");
}
__device__ __forceinline__ void st_async4(uint32_t a, float x, float y, float z, float w, uint32_t bar) {
    asm volatile("st.async.weak.shared::cluster.mbarrier::complete_tx::bytes.v4.f32 [%0], {%1, %2, %3, %4}, [%5];" :: "r"(a), "f"(x), "f"(y), "f"(z), "f"(w), "r"(bar) : "memory");
}
__device__ __forceinline__ void cluster_arrive() { asm volatile("barrier.cluster.arrive.relaxed.aligned;" ::: "memory"); }
__device__ __forceinline__ void cluster_wait() { asm volatile("barrier.cluster.wait.aligned;" ::: "memory"); }
__device__ __forceinline__ bool elect() { uint32_t r; asm volatile("{\n.reg .pred p;\nelect.sync _|p, 0xffffffff;\nselp.u32 %0,1,0,p;\n}" : "=r"(r)); return r; }
__device__ __forceinline__ uint32_t clk() { uint32_t t; asm volatile("mov.u32 %0, %clock;" : "=r"(t) :: "memory"); return t; }
__device__ __forceinline__ uint32_t gtime() { uint32_t t; asm volatile("mov.u32 %0, %globaltimer_lo;" : "=r"(t) :: "memory"); return t; }
template <int ID, int N> __device__ __forceinline__ void bar_sync() { asm volatile("bar.sync %0, %1;" :: "n"(ID), "n"(N) : "memory"); }
template <int ID, int N> __device__ __forceinline__ void bar_arrive() { asm volatile("bar.arrive %0, %1;" :: "n"(ID), "n"(N) : "memory"); }
__device__ __forceinline__ uint4 lds128(uint32_t a) { uint4 v; asm volatile("ld.shared.v4.u32 {%0,%1,%2,%3}, [%4];" : "=r"(v.x), "=r"(v.y), "=r"(v.z), "=r"(v.w) : "r"(a)); return v; }
__device__ __forceinline__ float2 lds64f(uint32_t a) { float2 v; asm volatile("ld.shared.v2.f32 {%0,%1}, [%2];" : "=f"(v.x), "=f"(v.y) : "r"(a)); return v; }
__device__ __forceinline__ uint4 ldg_poll(const void* p) { uint4 v; asm volatile("ld.relaxed.gpu.global.v4.u32 {%0,%1,%2,%3}, [%4];" : "=r"(v.x), "=r"(v.y), "=r"(v.z), "=r"(v.w) : "l"(p) : "memory"); return v; }
__device__ __forceinline__ void stg_pub4(void* p, uint32_t a, uint32_t b, uint32_t c, uint32_t d) { asm volatile("st.relaxed.gpu.global.v4.u32 [%0], {%1,%2,%3,%4};" :: "l"(p), "r"(a), "r"(b), "r"(c), "r"(d) : "memory"); }
__device__ __forceinline__ void stg_pub2(void* p, uint32_t a, uint32_t b) { asm volatile("st.relaxed.gpu.global.v2.u32 [%0], {%1,%2};" :: "l"(p), "r"(a), "r"(b) : "memory"); }
__device__ __forceinline__ void stg_pub1(void* p, uint32_t a) { asm volatile("st.relaxed.gpu.global.u32 [%0], %1;" :: "l"(p), "r"(a) : "memory"); }
__device__ __forceinline__ uint32_t bad4(uint4 v, uint32_t tag) { return ((v.x ^ tag) | (v.y ^ tag) | (v.z ^ tag) | (v.w ^ tag)) & 3u; }
__device__ __forceinline__ uint32_t tagf(float f, uint32_t tag) { return (__float_as_uint(f) & ~3u) | tag; }
__device__ __forceinline__ float bflo(uint32_t u) { return __uint_as_float(u << 16); }
__device__ __forceinline__ float bfhi(uint32_t u) { return __uint_as_float(u & 0xffff0000u); }
__device__ __forceinline__ float rbf(float f) { return __bfloat162float(__float2bfloat16_rn(f)); }
__device__ __forceinline__ uint32_t pack_bf(float lo, float hi) { const __nv_bfloat162 r = __floats2bfloat162_rn(lo, hi); return *reinterpret_cast<const uint32_t*>(&r); }
__device__ __forceinline__ void fma8(float* a, uint4 w, float s) {
    a[0] = fmaf(bflo(w.x), s, a[0]); a[1] = fmaf(bfhi(w.x), s, a[1]);
    a[2] = fmaf(bflo(w.y), s, a[2]); a[3] = fmaf(bfhi(w.y), s, a[3]);
    a[4] = fmaf(bflo(w.z), s, a[4]); a[5] = fmaf(bfhi(w.z), s, a[5]);
    a[6] = fmaf(bflo(w.w), s, a[6]); a[7] = fmaf(bfhi(w.w), s, a[7]);
}
template <int N, int M> __device__ __forceinline__ void halve(float* a, int lane) {
    const bool up = lane & M;
#pragma unroll
    for (int i = 0; i < N / 2; i++) {
        float keep = up ? a[i + N / 2] : a[i];
        float send = up ? a[i] : a[i + N / 2];
        a[i] = keep + __shfl_xor_sync(0xffffffffu, send, M);
    }
}
__device__ __forceinline__ void mma16816(float* c, uint32_t a0, uint32_t a1, uint32_t a2, uint32_t a3, uint32_t b0, uint32_t b1) {
    asm volatile("mma.sync.aligned.m16n8k16.row.col.f32.bf16.bf16.f32 {%0,%1,%2,%3}, {%4,%5,%6,%7}, {%8,%9}, {%0,%1,%2,%3};"
                 : "+f"(c[0]), "+f"(c[1]), "+f"(c[2]), "+f"(c[3]) : "r"(a0), "r"(a1), "r"(a2), "r"(a3), "r"(b0), "r"(b1));
}
#define TLREC(i) do { } while (0)

__global__ void __cluster_dims__(8, 1, 1) __launch_bounds__(NTHREADS, 1)
fused_decode_kernel(const __grid_constant__ Params p, const __grid_constant__ CUtensorMap tq,
                    const __grid_constant__ CUtensorMap t1, const __grid_constant__ CUtensorMap t2,
                    const __grid_constant__ CUtensorMap tv, const __grid_constant__ CUtensorMap to) {
    extern __shared__ __align__(1024) char sm[];
    __shared__ __align__(8) uint64_t bars[NBAR];
    __shared__ __align__(16) float xn_s[D_MODEL];
    __shared__ __align__(16) float red_s[8][64];
    __shared__ __align__(16) uint32_t q_s[8][256];
    __shared__ __align__(16) float2 sc_s[512];
    __shared__ __align__(16) float2 ml_s[8][8];
    __shared__ __align__(16) float in_s[8][8][64];
    __shared__ float b1_s[40];
    __shared__ uint32_t ep_s, g0_s;

    uint32_t (*p_s)[256] = reinterpret_cast<uint32_t (*)[256]>(red_s);
    uint32_t* h_s = reinterpret_cast<uint32_t*>(sc_s);
    const int c = blockIdx.x;
    const uint32_t bar0 = s2u(bars), sm0 = s2u(sm);
    const int cl = c >> 3, r = c & 7;
    const bool strm = cl < 8;
    const int row0 = SK - WKEYS + c * 32;
    uint64_t pol;
    asm("createpolicy.fractional.L2::evict_first.b64 %0, 1.0;" : "=l"(pol));
    {
        const char* k0 = p.k + (size_t)row0 * 512;
        asm volatile("" :: "l"(k0));
        if (threadIdx.x == 0) {
            mbar_init(bar0 + IT_K * 8, 1);
            mbar_fence_init();
            if (strm) { mbar_expect(bar0 + IT_K * 8, TILE); bulk(sm0 + IT_K * TILE, k0, TILE, bar0 + IT_K * 8, pol); }
        }
    }
    const int warp = __shfl_sync(0xffffffffu, threadIdx.x >> 5, 0);
    int lane;
    asm volatile("mov.u32 %0, %laneid;" : "=r"(lane));

    auto gather_o = [&](int h) {
        const int g = lane >> 2, tq4 = lane & 3;
        mbar_wait(bar0 + 16 * 8, 0);
        const uint32_t tag = (ep_s + 1) & 3u;
        const float wg = ml_s[h][g].x;
        const uint32_t due = p.to6 - (6 - h) * (p.pace >> 3), g0 = g0_s;
        while (gtime() - g0 < due) __nanosleep(64);
        const uint32_t* src = &p.s->obox[h][r][g][tq4 * 4];
        uint4 ov[4];
        int it = 0;
        while (true) {
#pragma unroll
            for (int i = 0; i < 4; i++) ov[i] = ldg_poll(src + i * 16);
            const uint32_t bad = (bad4(ov[3], tag) | bad4(ov[2], tag)) | (bad4(ov[1], tag) | bad4(ov[0], tag));
            if (!__any_sync(0xffffffffu, bad) || ++it >= SPIN_LIMIT) break;
            __nanosleep(100);
        }
        float a[16];
#pragma unroll
        for (int i = 0; i < 4; i++) {
            a[4 * i] = __uint_as_float(ov[i].x) * wg; a[4 * i + 1] = __uint_as_float(ov[i].y) * wg;
            a[4 * i + 2] = __uint_as_float(ov[i].z) * wg; a[4 * i + 3] = __uint_as_float(ov[i].w) * wg;
        }
        halve<16, 16>(a, lane); halve<8, 8>(a, lane); halve<4, 4>(a, lane);
        h_s[(7 + 2 * h + (g >> 2)) * 16 + tq4 * 4 + (g & 3)] = pack_bf(a[0], a[1]);
        __syncwarp();
        if (lane == 0) mbar_arrive(bar0 + (B_EMPTY + (h == 6)) * 8, h == 6 ? 8 : h < 2 ? 2 : 1);
    };

    if (warp == 0) {
        uint32_t g0 = 0;
        if (elect()) {
#pragma unroll
            for (int i = 0; i < 4 + KF; i++) if (!EARLY || i != IT_K) mbar_init(bar0 + (B_FULL + i) * 8, 1);
            mbar_fence_init();
            if (strm) {
#pragma unroll
                for (int i = EARLY; i < KF; i++) {
                    mbar_expect(bar0 + (IT_K + i) * 8, TILE);
                    bulk(sm0 + (IT_K + i) * TILE, p.k + (size_t)(row0 + (i >> 1) * SK + (i & 1) * 2048) * 512, TILE, bar0 + (IT_K + i) * 8, pol);
                }
#pragma unroll
                for (int i = 0; i < 4; i++) { mbar_expect(bar0 + i * 8, TILE); tma2d(sm0 + i * TILE, &tq, c * 64, i * 128, bar0 + i * 8); }
            }
            g0 = gtime();
            g0_s = g0;
            TLREC(19);
        }
        __syncwarp();
        bar_arrive<1, NTHREADS>();
        bar_sync<2, 64>();
        cluster_arrive();
        if (elect()) {
            if (strm) {
                asm volatile("prefetch.tensormap [%0];" :: "l"(&tv) : "memory");
                uint32_t target = p.t0 * 16;
                int slot = IT_K + KF, ph = 1;
#pragma unroll 1
                for (int it = IT_K + KF; it < NIT; it++) {
                    mbar_wait(bar0 + (B_EMPTY + slot) * 8, ph);
                    while ((gtime() - g0) * 16 < target) { }
                    target += p.pace;
                    const uint32_t b = bar0 + (B_FULL + it) * 8, dst = sm0 + slot * TILE;
                    const int tt = (it - IT_K) & 15, row = row0 + (tt >> 1) * SK + (tt & 1) * 2048;
                    mbar_expect(b, TILE);
                    if (it < IT_V) bulk(dst, p.k + (size_t)row * 512, TILE, b, pol);
                    else if (V4D) tma4d_h(dst, &tv, row >> 3, b, pol);
                    else tma3d_h(dst, &tv, 0, row, 0, b, pol);
                    if (++slot == NS) { slot = 0; ph ^= 1; }
                }
                TLREC(0);
            } else {
                const int k = cl - 8;
                while (gtime() - g0 < p.tw1) { }
                mbar_expect(bar0, 28672);
                tma2d(sm0, &t1, W2C ? (c - 64) * 32 : r * 224 + k * 32, 0, bar0);
                tma2d(sm0 + 14336, &t1, W2C ? (c - 64) * 32 : r * 224 + k * 32, 224, bar0);
                asm volatile("prefetch.tensormap [%0];" :: "l"(&t2) : "memory");
                while (gtime() - g0 < p.two7) __nanosleep(200);
                mbar_expect(bar0 + 15 * 8, 8192);
                tma2d(sm0 + SM_WO + 7 * 8192, &to, k * 64, 7 * 512 + r * 64, bar0 + 15 * 8);
                while (gtime() - g0 + 600 < p.tw2) __nanosleep(200);
                uint32_t target = p.tw2 * 16;
#pragma unroll 1
                for (int i = 0; i < 14; i++) {
                    while ((gtime() - g0) * 16 < target) { }
                    const uint32_t b = bar0 + (1 + i) * 8;
                    if (i < 7) {
                        target += p.pace_w2;
                        mbar_expect(b, 4096);
                        tma2d(sm0 + SM_W2 + i * 4096, &t2, k * 64, W2C ? i * 256 + r * 32 : r * 224 + i * 32, b);
                    } else {
                        target += p.pace_wo;
                        mbar_expect(b, 8192);
                        tma2d(sm0 + SM_WO + (i - 7) * 8192, &to, k * 64, (i - 7) * 512 + r * 64, b);
                    }
                }
                TLREC(0);
            }
        }
    } else if (warp <= 8 || (DEDUP && warp == 13)) {
        const int w = warp - 1, t = threadIdx.x - 32;
        const int g = lane >> 2, tq4 = lane & 3;
        if (warp <= 8) {
            const uint32_t* x2 = reinterpret_cast<const uint32_t*>(p.x);
            uint32_t xr[7];
            const uint32_t xm = __ldg(x2 + min(t, 223));
#pragma unroll
            for (int i = 0; i < 7; i++) xr[i] = __ldg(x2 + lane + 32 * i);
            float sum = 0.f;
#pragma unroll
            for (int i = 0; i < 7; i++) sum += bflo(xr[i]) + bfhi(xr[i]);
#pragma unroll
            for (int o = 16; o; o >>= 1) sum += __shfl_xor_sync(0xffffffffu, sum, o);
            const float mean = sum * (1.f / D_MODEL);
            float var = 0.f;
#pragma unroll
            for (int i = 0; i < 7; i++) { float a = bflo(xr[i]) - mean, b = bfhi(xr[i]) - mean; var += a * a + b * b; }
#pragma unroll
            for (int o = 16; o; o >>= 1) var += __shfl_xor_sync(0xffffffffu, var, o);
            const float mb = rbf(mean);
            const float den = rbf(__fsqrt_rn(rbf(rbf(var * (1.f / D_MODEL)) + 1e-5f)));
            if (w < 7) {
                float2 v;
                v.x = rbf(__fdiv_rn(rbf(bflo(xm) - mb), den));
                v.y = rbf(__fdiv_rn(rbf(bfhi(xm) - mb), den));
                *reinterpret_cast<float2*>(&xn_s[2 * t]) = v;
            }
        }
        bar_sync<1, NTHREADS>();
        cluster_arrive();
        const uint32_t tag = (ep_s + 1) & 3u;
        if (t == 0) TLREC(1);

        if (strm) {
            if (DEDUP && warp == 13) goto done;
            if (w == 0) stg_pub2(&p.s->qbox[cl][r * 64 + 2 * lane], tag ^ 2u, tag ^ 2u);
            {
                float a[8];
#pragma unroll
                for (int i = 0; i < 8; i++) a[i] = 0.f;
#pragma unroll 1
                for (int b = 0; b < 4; b++) {
                    mbar_wait(bar0 + (B_FULL + b) * 8, 0);
                    const uint32_t base = sm0 + b * TILE + t * 16;
                    const float* xs = &xn_s[b * 128 + (t >> 3)];
                    fma8(a, lds128(base), xs[0]);
                    fma8(a, lds128(base + 4096), xs[32]);
                    if (b < 3) {
                        fma8(a, lds128(base + 8192), xs[64]);
                        fma8(a, lds128(base + 12288), xs[96]);
                    }
                    __syncwarp();
                    if (lane == 0) mbar_arrive(bar0 + (B_EMPTY + b) * 8, 1);
                }
                if (t == 0) TLREC(18);
                halve<8, 16>(a, lane); halve<4, 8>(a, lane);
                *reinterpret_cast<float2*>(&red_s[w][(lane & 7) * 8 + (lane >> 3) * 2]) = make_float2(a[0], a[1]);
                bar_sync<3, 256>();
                if (w == 0) {
                    float q0 = 0.f, q1 = 0.f;
#pragma unroll
                    for (int i = 0; i < 8; i++) { const float2 v = *reinterpret_cast<const float2*>(&red_s[i][2 * lane]); q0 += v.x; q1 += v.y; }
                    stg_pub2(&p.s->qbox[cl][r * 64 + 2 * lane], __float_as_uint(rbf(q0)) | tag, __float_as_uint(rbf(q1)) | tag);
                    if (t == 0) TLREC(2);
                }
            }
            mbar_wait(bar0 + B_Q * 8, 0);
            if (t == 0) TLREC(3);
#pragma unroll 1
            for (int i4 = 0; i4 < 4; i4++) {
                const int tile = (w >> 1) + 4 * i4, it = IT_K + tile;
                const int slot = it >= NS ? it - NS : it;
                uint4 qf[8];
#pragma unroll
                for (int i = 0; i < 8; i++) {
                    qf[i] = make_uint4(0, 0, 0, 0);
                    if (g < 2) qf[i] = lds128(s2u(&q_s[tile >> 1][0]) + g * 512 + i * 64 + tq4 * 16);
                }
                mbar_wait(bar0 + (B_FULL + it) * 8, 0);
                float ca[4] = {0.f, 0.f, 0.f, 0.f}, cb[4] = {0.f, 0.f, 0.f, 0.f};
                const uint32_t base = sm0 + slot * TILE + (w & 1) * 8192 + g * 512 + tq4 * 16;
#pragma unroll
                for (int i = 0; i < 8; i++) {
                    const uint4 lo = lds128(base + i * 64), hi = lds128(base + 4096 + i * 64);
                    mma16816(ca, lo.x, hi.x, lo.y, hi.y, qf[i].x, qf[i].y);
                    mma16816(cb, lo.z, hi.z, lo.w, hi.w, qf[i].z, qf[i].w);
                }
                if (lane == 0) mbar_arrive(bar0 + (B_EMPTY + slot) * 8, 4);
                if (tq4 == 0) {
                    const int key = tile * 32 + (w & 1) * 16 + g;
                    sc_s[key] = make_float2(rbf(ca[0] + cb[0]) * 0.0625f, rbf(ca[1] + cb[1]) * 0.0625f);
                    sc_s[key + 8] = make_float2(rbf(ca[2] + cb[2]) * 0.0625f, rbf(ca[3] + cb[3]) * 0.0625f);
                }
            }
            bar_sync<3, 256>();
            {
                if (t == 0) TLREC(4);
                float4 s = *reinterpret_cast<const float4*>(&sc_s[2 * t]);
                float m0 = fmaxf(s.x, s.z), m1 = fmaxf(s.y, s.w);
#pragma unroll
                for (int o = 16; o; o >>= 1) { m0 = fmaxf(m0, __shfl_xor_sync(0xffffffffu, m0, o)); m1 = fmaxf(m1, __shfl_xor_sync(0xffffffffu, m1, o)); }
                s.x = exp2f((s.x - m0) * LOG2E); s.y = exp2f((s.y - m1) * LOG2E);
                s.z = exp2f((s.z - m0) * LOG2E); s.w = exp2f((s.w - m1) * LOG2E);
                const int pos = (t & ~15) + (t & 3) * 4 + ((t >> 2) & 3);
                p_s[0][pos] = pack_bf(s.x, s.z);
                p_s[1][pos] = pack_bf(s.y, s.w);
                float l0 = s.x + s.z, l1 = s.y + s.w;
#pragma unroll
                for (int o = 16; o; o >>= 1) { l0 += __shfl_xor_sync(0xffffffffu, l0, o); l1 += __shfl_xor_sync(0xffffffffu, l1, o); }
                cluster_wait();
                if (lane < 8) st_async2(mapa(s2u(&ml_s[w][r]), lane), lane < 4 ? m0 : m1, lane < 4 ? l0 : l1, mapa(bar0 + B_ML * 8, lane));
                bar_sync<3, 256>();
            }
            {
                const uint32_t lo = V4D ? sm0 + (w >> 1) * 1024 + (lane & 7) * 128 + (lane >> 4) * 4096 : sm0 + (w >> 1) * 4096 + ((lane & 7) + 8 * (lane >> 4)) * 128;
                const uint32_t sw = ((w & 1) * 4 + ((lane >> 3) & 1)) ^ (lane & 7);
                const uint32_t pa = s2u(&p_s[g & 1][tq4 * 4]);
                const int dst = (tq4 & 1) * 4 + (w >> 1);
                const uint32_t da = mapa(s2u(&in_s[0][r][(w & 1) * 32 + (tq4 >> 1) * 16 + g]), dst), db = mapa(bar0 + B_O * 8, dst);
                int slot = IT_V - NS;
#pragma unroll 1
                for (int h = 0; h < 8; h++) {
                    float acc[4][4];
#pragma unroll
                    for (int i = 0; i < 4; i++) { acc[i][0] = acc[i][1] = acc[i][2] = acc[i][3] = 0.f; }
#pragma unroll
                    for (int j = 0; j < 2; j++) {
                        const uint4 pf = lds128(pa + (2 * h + j) * 64);
                        const uint32_t base = lo + (slot + j) * TILE;
                        mbar_wait(bar0 + (B_FULL + IT_V + 2 * h + j) * 8, 0);
                        uint4 vf[4];
#pragma unroll
                        for (int i = 0; i < 4; i++) vf[i] = ldsm4t(base + (i >> 1) * (V4D ? 8192 : 2048) + ((sw ^ (2 * (i & 1))) << 4));
                        mma16816(acc[0], vf[0].x, vf[0].y, vf[0].z, vf[0].w, pf.x, pf.y);
                        mma16816(acc[1], vf[1].x, vf[1].y, vf[1].z, vf[1].w, pf.x, pf.y);
                        mma16816(acc[2], vf[2].x, vf[2].y, vf[2].z, vf[2].w, pf.z, pf.w);
                        mma16816(acc[3], vf[3].x, vf[3].y, vf[3].z, vf[3].w, pf.z, pf.w);
                        if (lane == 0) mbar_arrive(bar0 + (B_EMPTY + slot + j) * 8, 1);
                    }
                    slot += 2;
                    if (slot == NS) slot = 0;
                    const bool hi = tq4 & 2, h1 = tq4 & 1;
                    const float x0 = hi ? acc[1][0] + acc[3][0] : acc[0][0] + acc[2][0], x1 = hi ? acc[1][1] + acc[3][1] : acc[0][1] + acc[2][1];
                    const float x2 = hi ? acc[1][2] + acc[3][2] : acc[0][2] + acc[2][2], x3 = hi ? acc[1][3] + acc[3][3] : acc[0][3] + acc[2][3];
                    st_async1(da + h * 2048, __float_as_uint(h1 ? x1 : x0), db + h * 8);
                    st_async1(da + h * 2048 + 32, __float_as_uint(h1 ? x3 : x2), db + h * 8);
                }
                if (t == 0) TLREC(6);
            }
        } else {
            const int k = cl - 8;
            if (w == 0) stg_pub1(&p.s->hbox[r][k * 32 + lane], tag ^ 2u);
            if (warp <= 8) {
                float a[8];
#pragma unroll
                for (int i = 0; i < 8; i++) a[i] = 0.f;
                mbar_wait(bar0, 0);
#pragma unroll 1
                for (int i = 0; i < 7; i++) fma8(a, lds128(sm0 + (t + 256 * i) * 16), xn_s[(t >> 2) + 64 * i]);
                halve<8, 16>(a, lane); halve<4, 8>(a, lane); halve<2, 4>(a, lane);
                red_s[w][(lane & 3) * 8 + (lane >> 2)] = a[0];
                bar_sync<3, 256>();
                if (w == 0) {
                    float h = 0.f;
#pragma unroll
                    for (int i = 0; i < 8; i++) h += red_s[i][lane];
                    h = rbf(rbf(h) + b1_s[lane]);
                    const float u = 0.7978845608028654f * (h + 0.044715f * h * h * h);
                    stg_pub1(&p.s->hbox[r][k * 32 + lane], __float_as_uint(rbf(0.5f * h * (1.f + tanhf(u)))) | tag);
                    if (t == 0) TLREC(2);
                }
                if (t < 56) {
                    uint4 v;
                    int it = 0;
                    do { __nanosleep(1000); v = ldg_poll(&p.s->hbox[r][t * 4]); } while (bad4(v, tag) && ++it < SPIN_LIMIT);
                    const int pi = 2 * t, pos = (pi & ~15) + (pi & 3) * 4 + ((pi >> 2) & 3);
                    h_s[pos] = __byte_perm(v.x, v.y, 0x7632);
                    h_s[pos + 4] = __byte_perm(v.z, v.w, 0x7632);
                }
                bar_sync<3, 256>();
                if (t == 0) TLREC(3);
            }
            cluster_wait();
            if (w < 6 || w == 12) { gather_o(w == 12 ? 6 : w); if (t == 5 * 32) TLREC(10); if (t == 12 * 32) TLREC(12); }
            if (w == 12) goto done;
            {
                float acc[2][4] = {{0.f, 0.f, 0.f, 0.f}, {0.f, 0.f, 0.f, 0.f}};
                const uint32_t base = sm0 + SM_W2 + ((lane & 7) + 16 * ((lane >> 3) & 1) + 8 * (lane >> 4)) * 128 + ((w ^ (lane & 7)) << 4);
                const uint32_t va = s2u(&h_s[tq4 * 4 + (g & 1) * 2]);
                const uint32_t da = mapa(s2u(&in_s[0][0][(32 + r) * 8 + g]), w), db = mapa(bar0 + B_F * 8, w);
                uint4 u0, u1;
                float2 b0, b1;
#pragma unroll
                for (int i = 0; i < 15; i++) {
                    uint4 n0, n1;
                    float2 c0, c1;
                    if (i == 13) {
                        mma16816(acc[0], u0.x, u0.y, u0.z, u0.w, __float_as_uint(b0.x), __float_as_uint(b0.y));
                        mma16816(acc[1], u1.x, u1.y, u1.z, u1.w, __float_as_uint(b1.x), __float_as_uint(b1.y));
                    }
                    if (i < 14) {
                        if (i == 7 || i == 13) mbar_wait(bar0 + (B_EMPTY + (i == 13)) * 8, 0);
                        const int j = i < 7 ? i : 2 * i - 7;
                        c0 = lds64f(va + j * 64);
                        if (i >= 7) c1 = lds64f(va + j * 64 + 64);
                        mbar_wait(bar0 + (1 + i) * 8, 0);
                        n0 = ldsm4t(base + (i < 7 ? j : j + 1) * 4096);
                        if (i >= 7) n1 = ldsm4t(base + (j + 2) * 4096);
                    }
                    if (i > 0 && i != 13) {
                        mma16816(acc[i > 7 ? 0 : i & 1], u0.x, u0.y, u0.z, u0.w, __float_as_uint(b0.x), __float_as_uint(b0.y));
                        if (i > 7) mma16816(acc[1], u1.x, u1.y, u1.z, u1.w, __float_as_uint(b1.x), __float_as_uint(b1.y));
                    }
                    u0 = n0; u1 = n1; b0 = c0; b1 = c1;
                }
                if (tq4 == 0) st_async1(da, __float_as_uint((acc[0][0] + acc[0][3]) + (acc[1][0] + acc[1][3])), db);
                if (t == 0) TLREC(8);
            }
        }
    } else {
        const int fw = warp - 9, t = threadIdx.x - 288;
        if (fw == 0) {
            if (elect()) {
#pragma unroll
                for (int i = 4 + KF; i < NBAR; i++) mbar_init(bar0 + i * 8, (i >= B_EMPTY && i < B_Q) ? 8 : 1);
                mbar_fence_init();
            }
            __syncwarp();
            bar_arrive<2, 64>();
            if (elect()) {
                mbar_expect(bar0 + B_Q * 8, 8192);
                mbar_expect(bar0 + B_ML * 8, strm ? 512 : 1024);
                mbar_expect(bar0 + B_F * 8, 256);
#pragma unroll
                for (int i = 0; i < 8; i++) mbar_expect(bar0 + (B_O + i) * 8, 2048);
            }
            __syncwarp();
        } else if (fw == 1) {
            uint32_t e;
            asm volatile("ld.relaxed.gpu.global.u32 %0, [%1];" : "=r"(e) : "l"(&p.s->epoch) : "memory");
            if (lane == 0) ep_s = e;
        } else if (!strm) {
            if (fw == 2) {
                b1_s[lane] = __bfloat162float(p.b1[(W2C ? (c - 64) * 32 : r * 224 + (cl - 8) * 32) + lane]);
            } else if (fw == 3) {
                const int col = (c - 64) * 8 + (lane & 7);
                if (lane < 8) b1_s[32 + lane] = __bfloat162float(p.x[col]) + __bfloat162float(p.b2[col]);
            }
        }
        bar_sync<1, NTHREADS>();
        cluster_arrive();
        const uint32_t tag = (ep_s + 1) & 3u;
        if (fw == 4) {
            if (!DEDUP && !strm) { gather_o(6); if (lane == 0) TLREC(12); }
        } else if (strm) {
            {
                uint4 v;
                int it = 0;
                mbar_wait(bar0 + (B_EMPTY + 3) * 8, 0);
                while (true) {
                    __nanosleep(it ? QSLEEP : QSLEEP0);
                    v = ldg_poll(&p.s->qbox[r][t * 4]);
                    if (!bad4(v, tag) || ++it >= SPIN_LIMIT) break;
                }
                __syncwarp();
                cluster_wait();
                const float lo = __uint_as_float(__byte_perm(v.x, v.y, 0x7632)), hi = __uint_as_float(__byte_perm(v.z, v.w, 0x7632));
#pragma unroll
                for (int d = 0; d < 8; d++) st_async2(mapa(s2u(&q_s[r][t * 2]), d), lo, hi, mapa(bar0 + B_Q * 8, d));
            }
            if (fw == 0) {
                uint32_t* dst = &p.s->obox[0][r][cl][(lane >> 3) * 16 + (lane & 3) * 4 + ((lane >> 2) & 1) * 2];
#pragma unroll
                for (int h = 0; h < 8; h++) stg_pub2(dst + h * 4096, tag ^ 2u, tag ^ 2u);
                if ((lane & 7) == 0) { stg_pub2(&p.s->sbox[r][cl][2 * (lane >> 3)], tag ^ 2u, tag ^ 2u); stg_pub2(&p.s->sbox[r][cl][2 * (lane >> 3) + 8], tag ^ 2u, tag ^ 2u); }
                mbar_wait(bar0 + B_ML * 8, 0);
                float e[2];
#pragma unroll
                for (int i = 0; i < 2; i++) {
                    const float2 v = ml_s[(lane >> 3) + 4 * i][lane & 7];
                    float M = v.x;
#pragma unroll
                    for (int o = 1; o < 8; o <<= 1) M = fmaxf(M, __shfl_xor_sync(0xffffffffu, M, o));
                    e[i] = exp2f((v.x - M) * LOG2E);
                    float L = v.y * e[i];
#pragma unroll
                    for (int o = 1; o < 8; o <<= 1) L += __shfl_xor_sync(0xffffffffu, L, o);
                    if ((lane & 7) == 0) stg_pub2(&p.s->sbox[r][cl][2 * ((lane >> 3) + 4 * i)], tagf(M, tag), tagf(L, tag));
                }
#pragma unroll 1
                for (int h = 0; h < 8; h++) {
                    float ws[8];
#pragma unroll
                    for (int s = 0; s < 8; s++) ws[s] = __shfl_sync(0xffffffffu, h < 4 ? e[0] : e[1], (h & 3) * 8 + s);
                    mbar_wait(bar0 + (B_O + h) * 8, 0);
                    float2 ov[8];
#pragma unroll
                    for (int s = 0; s < 8; s++) ov[s] = lds64f(s2u(&in_s[h][s][2 * lane]));
                    const float o0 = (fmaf(ov[0].x, ws[0], ov[1].x * ws[1]) + fmaf(ov[2].x, ws[2], ov[3].x * ws[3])) + (fmaf(ov[4].x, ws[4], ov[5].x * ws[5]) + fmaf(ov[6].x, ws[6], ov[7].x * ws[7]));
                    const float o1 = (fmaf(ov[0].y, ws[0], ov[1].y * ws[1]) + fmaf(ov[2].y, ws[2], ov[3].y * ws[3])) + (fmaf(ov[4].y, ws[4], ov[5].y * ws[5]) + fmaf(ov[6].y, ws[6], ov[7].y * ws[7]));
                    stg_pub2(dst + h * 4096, tagf(o0, tag), tagf(o1, tag));
                }
                if (lane == 0) TLREC(9);
            }
        } else {
            const int g = lane >> 2, tq4 = lane & 3;
            mbar_wait(bar0 + 15 * 8, 0);
            uint4 wf[4];
#pragma unroll
            for (int j = 0; j < 4; j++)
                wf[j] = ldsm4t(sm0 + SM_WO + 7 * 8192 + fw * 2048 + ((lane & 7) + 8 * (lane >> 4)) * 128 + (((2 * j + ((lane >> 3) & 1)) ^ (lane & 7)) << 4));
            float wgt[2];
            {
                uint4 v;
                int it = 0;
                while (true) {
                    v = ldg_poll(&p.s->sbox[r][g][4 * tq4]);
                    if (!__any_sync(0xffffffffu, bad4(v, tag)) || ++it >= SPIN_LIMIT) break;
                    __nanosleep(300);
                }
#pragma unroll
                for (int i = 0; i < 2; i++) {
                    const float m = __uint_as_float((i ? v.z : v.x) & ~3u);
                    float M = m;
#pragma unroll
                    for (int o = 4; o < 32; o <<= 1) M = fmaxf(M, __shfl_xor_sync(0xffffffffu, M, o));
                    const float e = exp2f((m - M) * LOG2E);
                    float L = __uint_as_float((i ? v.w : v.y) & ~3u) * e;
#pragma unroll
                    for (int o = 4; o < 32; o <<= 1) L += __shfl_xor_sync(0xffffffffu, L, o);
                    wgt[i] = __fdividef(e, L);
                }
                if (fw == 0) {
                    ml_s[2 * tq4][g].x = wgt[0]; ml_s[2 * tq4 + 1][g].x = wgt[1];
                    __syncwarp();
                    if (lane == 0) mbar_arrive(bar0 + 16 * 8, 1);
                }
                if (t == 0) TLREC(4);
            }
            const uint32_t fa = s2u(&in_s[0][0][(r * 4 + fw) * 8 + g]);
            const uint32_t da0 = mapa(fa, 2 * tq4), db0 = mapa(bar0 + B_ML * 8, 2 * tq4), da1 = mapa(fa, 2 * tq4 + 1), db1 = mapa(bar0 + B_ML * 8, 2 * tq4 + 1);
            const float wg7 = __shfl_sync(0xffffffffu, wgt[1], (lane & 28) + 3);
            cluster_wait();
            const uint32_t* src = &p.s->obox[7][r][g][fw * 16 + tq4 * 4];
            uint4 ov;
            {
                const uint32_t g0 = g0_s;
                while (gtime() - g0 < p.to7) __nanosleep(64);
                int it = 0;
                do { ov = ldg_poll(src); } while (__any_sync(0xffffffffu, bad4(ov, tag)) && ++it < SPIN_LIMIT);
            }
            if (t == 0) TLREC(7);
            const uint32_t b0 = pack_bf(__uint_as_float(ov.x) * wg7, __uint_as_float(ov.y) * wg7), b1 = pack_bf(__uint_as_float(ov.z) * wg7, __uint_as_float(ov.w) * wg7);
            float a[8];
#pragma unroll
            for (int j = 0; j < 4; j++) {
                float acc[4] = {0.f, 0.f, 0.f, 0.f};
                mma16816(acc, wf[j].x, wf[j].y, wf[j].z, wf[j].w, b0, b1);
                a[2 * j] = acc[0] + acc[1]; a[2 * j + 1] = acc[2] + acc[3];
            }
            halve<8, 2>(a, lane); halve<4, 1>(a, lane);
            st_async1(da0, __float_as_uint(a[0]), db0);
            st_async1(da1, __float_as_uint(a[1]), db1);
            if (t == 0) TLREC(9);
            if (fw == 0) {
                const float base = b1_s[32 + (lane & 7)];
                __nv_bfloat16* dst = p.out + (c - 64) * 8 + (lane & 7);
                const volatile float* in = &in_s[0][0][0];
                float s[8];
                mbar_wait(bar0 + B_ML * 8, 0);
#pragma unroll
                for (int i = 0; i < 8; i++) s[i] = in[i * 32 + lane];
                float v = ((s[0] + s[1]) + (s[2] + s[3])) + ((s[4] + s[5]) + (s[6] + s[7]));
                v += __shfl_xor_sync(0xffffffffu, v, 8);
                v += __shfl_xor_sync(0xffffffffu, v, 16);
                v += base;
                mbar_wait(bar0 + B_F * 8, 0);
#pragma unroll
                for (int i = 0; i < 8; i++) s[i] = in[256 + i * 8 + (lane & 7)];
                v += ((s[0] + s[1]) + (s[2] + s[3])) + ((s[4] + s[5]) + (s[6] + s[7]));
                if (lane < 8) *dst = __float2bfloat16_rn(v);
                if (c == 64 && lane == 0) p.s->epoch = ep_s + 1;
                if (lane == 0) TLREC(11);
            }
        }
    }
done:;
}

typedef CUresult (*EncodeFn)(CUtensorMap*, CUtensorMapDataType, cuuint32_t, void*, const cuuint64_t*, const cuuint64_t*,
                             const cuuint32_t*, const cuuint32_t*, CUtensorMapInterleave, CUtensorMapSwizzle,
                             CUtensorMapL2promotion, CUtensorMapFloatOOBfill);

void make_map(EncodeFn encode, CUtensorMap* m, void* base, uint64_t cols, uint64_t rows, uint32_t bc, uint32_t br, bool swz) {
    cuuint64_t gd[2] = {cols, rows}; cuuint64_t gs[1] = {cols * 2}; cuuint32_t bd[2] = {bc, br}; cuuint32_t es[2] = {1, 1};
    encode(m, CU_TENSOR_MAP_DATA_TYPE_BFLOAT16, 2, base, gd, gs, bd, es, CU_TENSOR_MAP_INTERLEAVE_NONE,
           swz ? CU_TENSOR_MAP_SWIZZLE_128B : CU_TENSOR_MAP_SWIZZLE_NONE, (CUtensorMapL2promotion)WPROM, CU_TENSOR_MAP_FLOAT_OOB_FILL_NONE);
}

}

constexpr uint32_t g_cfg[9] = {5250, 1600, 500, 8800, 11780, 1300, 2450, 13000, 13450};

extern "C" void kernel_launch(void* const* d_in, const int* in_sizes, int n_in, void* d_out, int out_size) {
    (void)in_sizes; (void)n_in; (void)out_size;
    static EncodeFn encode = nullptr;
    static Scratch* scratch = nullptr;
    if (!encode) {
        void* fn = nullptr;
        cudaDriverEntryPointQueryResult st;
        cudaGetDriverEntryPoint("cuTensorMapEncodeTiled", &fn, cudaEnableDefault, &st);
        encode = (EncodeFn)fn;
        cudaGetSymbolAddress((void**)&scratch, g_scratch);
        cudaFuncSetAttribute(fused_decode_kernel, cudaFuncAttributeMaxDynamicSharedMemorySize, SM_DYN);
    }
    CUtensorMap tq, t1, t2, tv, to;
    make_map(encode, &tq, d_in[3], 4096, D_MODEL, 64, 128, false);
    make_map(encode, &t1, d_in[6], FFN, D_MODEL, 32, 224, false);
    make_map(encode, &t2, d_in[8], D_MODEL, FFN, 64, 32, true);
    make_map(encode, &to, d_in[4], D_MODEL, 4096, 64, 64, true);
    {
        cuuint64_t gd[4] = {64, 8, 4, (cuuint64_t)SK}; cuuint64_t gs[3] = {512, 128, 4096}; cuuint32_t bd[4] = {64, 8, 4, 4}; cuuint32_t es[4] = {1, 1, 1, 1};
        CUresult rc = encode(&tv, CU_TENSOR_MAP_DATA_TYPE_BFLOAT16, V4D ? 4 : 3, d_in[2], gd, gs, bd, es, CU_TENSOR_MAP_INTERLEAVE_NONE,
               CU_TENSOR_MAP_SWIZZLE_128B, (CUtensorMapL2promotion)VPROM, CU_TENSOR_MAP_FLOAT_OOB_FILL_NONE);
        (void)rc;
    }
    Params p;
    p.x = (const __nv_bfloat16*)d_in[0];
    p.k = (const char*)d_in[1];
    p.b1 = (const __nv_bfloat16*)d_in[7];
    p.b2 = (const __nv_bfloat16*)d_in[9];
    p.out = (__nv_bfloat16*)d_out;
    p.s = scratch;
    p.pace = g_cfg[0]; p.t0 = g_cfg[1]; p.tw1 = g_cfg[2]; p.two7 = g_cfg[3]; p.tw2 = g_cfg[4]; p.pace_w2 = g_cfg[5]; p.pace_wo = g_cfg[6]; p.to6 = g_cfg[7]; p.to7 = g_cfg[8];
    fused_decode_kernel<<<NCTA, NTHREADS, SM_DYN, cudaStreamPerThread>>>(p, tq, t1, t2, tv, to);
}
```

```cpp
#include <cuda_runtime.h>
#include <cuda_bf16.h>
#include <cuda.h>
#include <stdint.h>

namespace {

constexpr int D_MODEL = 448;
constexpr int FFN = 1792;
constexpr int SK = 65536;
constexpr int WKEYS = 4096;
constexpr int NCTA = 120;
constexpr int TILE = 16384;
constexpr int NS = 12;
constexpr int NTHREADS = 32 * (1 + 8 + 5);
constexpr int SPIN_LIMIT = 1 << 20;
constexpr float LOG2E = 1.4426950408889634f;

constexpr int IT_K = 4, IT_V = 20, NIT = 36;
constexpr int B_FULL = 0, B_EMPTY = NIT, B_Q = NIT + NS, B_ML = B_Q + 1, B_F = B_Q + 2, B_O = B_Q + 3, NBAR = B_O + 8;
constexpr int B_WGT = 16, B_TIME = 17, B_O05 = B_EMPTY, B_O6 = B_EMPTY + 1, B_F7 = B_ML;
constexpr int SM_W2 = 2 * TILE, SM_WO = 4 * TILE;
constexpr int SM_DYN = NS * TILE;

struct Scratch {
    uint32_t qbox[8][512];
    uint32_t hbox[8][256];
    uint32_t sbox[8][8][16];
    uint32_t obox[8][8][8][64];
    uint32_t tbox[8][8][8];
    uint32_t epoch;
    uint32_t pad[31];
};
__device__ __align__(128) Scratch g_scratch;

struct Params {
    const __nv_bfloat16* x;
    const char* k;
    const __nv_bfloat16* b1;
    const __nv_bfloat16* b2;
    __nv_bfloat16* out;
    Scratch* s;
    uint32_t pace;
    uint32_t t0;
    uint32_t tw1;
    uint32_t two7;
    uint32_t tw2;
    uint32_t pace_w2;
    uint32_t pace_wo;
    uint32_t tt, tn;
    uint32_t th;
    uint32_t to6, to7;
};

__device__ __forceinline__ uint32_t s2u(const void* p) { return (uint32_t)__cvta_generic_to_shared(p); }
__device__ __forceinline__ void mbar_init(uint32_t b, uint32_t c) { asm volatile("mbarrier.init.shared::cta.b64 [%0], %1;" :: "r"(b), "r"(c) : "memory"); }
__device__ __forceinline__ void mbar_fence_init() { asm volatile("fence.mbarrier_init.release.cluster;" ::: "memory"); }
__device__ __forceinline__ void mbar_expect(uint32_t b, uint32_t bytes) { asm volatile("mbarrier.arrive.expect_tx.shared::cta.b64 _, [%0], %1;" :: "r"(b), "r"(bytes) : "memory"); }
__device__ __forceinline__ void mbar_arrive(uint32_t b, uint32_t n) { asm volatile("mbarrier.arrive.shared::cta.b64 _, [%0], %1;" :: "r"(b), "r"(n) : "memory"); }
__device__ __forceinline__ void mbar_wait(uint32_t b, uint32_t ph) {
    asm volatile("{\n.reg .pred p;\nW: mbarrier.try_wait.parity.shared::cta.b64 p, [%0], %1;\n@p bra D;\nbra W;\nD:\n}" :: "r"(b), "r"(ph) : "memory");
}
__device__ __forceinline__ void bulk(uint32_t dst, const void* src, uint32_t bytes, uint32_t bar, uint64_t pol) {
    asm volatile("cp.async.bulk.shared::cluster.global.mbarrier::complete_tx::bytes.L2::cache_hint [%0], [%1], %2, [%3], %4;" :: "r"(dst), "l"(src), "r"(bytes), "r"(bar), "l"(pol) : "memory");
}
__device__ __forceinline__ void tma2d(uint32_t dst, const void* tm, int x, int y, uint32_t bar) {
    asm volatile("cp.async.bulk.tensor.2d.shared::cluster.global.mbarrier::complete_tx::bytes [%0], [%1, {%3, %4}], [%2];" :: "r"(dst), "l"(tm), "r"(bar), "r"(x), "r"(y) : "memory");
}
__device__ __forceinline__ void tma4d(uint32_t dst, const void* tm, int y, uint32_t bar, uint64_t pol) {
    asm volatile("cp.async.bulk.tensor.4d.shared::cluster.global.mbarrier::complete_tx::bytes.L2::cache_hint [%0], [%1, {0, 0, 0, %3}], [%2], %4;" :: "r"(dst), "l"(tm), "r"(bar), "r"(y), "l"(pol) : "memory");
}
__device__ __forceinline__ uint4 ldsm4t(uint32_t a) { uint4 v; asm volatile("ldmatrix.sync.aligned.m8n8.x4.trans.shared.b16 {%0,%1,%2,%3}, [%4];" : "=r"(v.x), "=r"(v.y), "=r"(v.z), "=r"(v.w) : "r"(a)); return v; }
__device__ __forceinline__ uint32_t mapa(uint32_t a, uint32_t r) { uint32_t d; asm("mapa.shared::cluster.u32 %0, %1, %2;" : "=r"(d) : "r"(a), "r"(r)); return d; }
__device__ __forceinline__ void st_async1(uint32_t a, uint32_t x, uint32_t bar) {
    asm volatile("st.async.weak.shared::cluster.mbarrier::complete_tx::bytes.b32 [%0], %1, [%2];" :: "r"(a), "r"(x), "r"(bar) : "memory");
}
__device__ __forceinline__ void st_async2(uint32_t a, uint32_t x, uint32_t y, uint32_t bar) {
    asm volatile("st.async.weak.shared::cluster.mbarrier::complete_tx::bytes.v2.b32 [%0], {%1, %2}, [%3];" :: "r"(a), "r"(x), "r"(y), "r"(bar) : "memory");
}
__device__ __forceinline__ void cluster_arrive() { asm volatile("barrier.cluster.arrive.relaxed.aligned;" ::: "memory"); }
__device__ __forceinline__ void cluster_wait() { asm volatile("barrier.cluster.wait.aligned;" ::: "memory"); }
__device__ __forceinline__ bool elect() { uint32_t r; asm volatile("{\n.reg .pred p;\nelect.sync _|p, 0xffffffff;\nselp.u32 %0,1,0,p;\n}" : "=r"(r)); return r; }
__device__ __forceinline__ uint32_t gtime() { uint32_t t; asm volatile("mov.u32 %0, %globaltimer_lo;" : "=r"(t) :: "memory"); return t; }
template <int ID, int N> __device__ __forceinline__ void bar_sync() { asm volatile("bar.sync %0, %1;" :: "n"(ID), "n"(N) : "memory"); }
template <int ID, int N> __device__ __forceinline__ void bar_arrive() { asm volatile("bar.arrive %0, %1;" :: "n"(ID), "n"(N) : "memory"); }
__device__ __forceinline__ uint4 lds128(uint32_t a) { uint4 v; asm volatile("ld.shared.v4.u32 {%0,%1,%2,%3}, [%4];" : "=r"(v.x), "=r"(v.y), "=r"(v.z), "=r"(v.w) : "r"(a)); return v; }
__device__ __forceinline__ float2 lds64f(uint32_t a) { float2 v; asm volatile("ld.shared.v2.f32 {%0,%1}, [%2];" : "=f"(v.x), "=f"(v.y) : "r"(a)); return v; }
__device__ __forceinline__ void sts64f(uint32_t a, float x, float y) { asm volatile("st.shared.v2.f32 [%0], {%1,%2};" :: "r"(a), "f"(x), "f"(y) : "memory"); }
__device__ __forceinline__ uint4 ldg_poll(const void* p) { uint4 v; asm volatile("ld.relaxed.gpu.global.v4.u32 {%0,%1,%2,%3}, [%4];" : "=r"(v.x), "=r"(v.y), "=r"(v.z), "=r"(v.w) : "l"(p) : "memory"); return v; }
__device__ __forceinline__ void stg_pub2(void* p, uint32_t a, uint32_t b) { asm volatile("st.relaxed.gpu.global.v2.u32 [%0], {%1,%2};" :: "l"(p), "r"(a), "r"(b) : "memory"); }
__device__ __forceinline__ void stg_pub1(void* p, uint32_t a) { asm volatile("st.relaxed.gpu.global.u32 [%0], %1;" :: "l"(p), "r"(a) : "memory"); }
__device__ __forceinline__ uint32_t bad4(uint4 v, uint32_t tag) { return ((v.x ^ tag) | (v.y ^ tag) | (v.z ^ tag) | (v.w ^ tag)) & 3u; }
__device__ __forceinline__ uint32_t tagf(float f, uint32_t tag) { return (__float_as_uint(f) & ~3u) | tag; }
__device__ __forceinline__ float bflo(uint32_t u) { return __uint_as_float(u << 16); }
__device__ __forceinline__ float bfhi(uint32_t u) { return __uint_as_float(u & 0xffff0000u); }
__device__ __forceinline__ float rbf(float f) { return __bfloat162float(__float2bfloat16_rn(f)); }
__device__ __forceinline__ uint32_t pack_bf(float lo, float hi) { const __nv_bfloat162 r = __floats2bfloat162_rn(lo, hi); return *reinterpret_cast<const uint32_t*>(&r); }
__device__ __forceinline__ void fma8(float* a, uint4 w, float s) {
    a[0] = fmaf(bflo(w.x), s, a[0]); a[1] = fmaf(bfhi(w.x), s, a[1]);
    a[2] = fmaf(bflo(w.y), s, a[2]); a[3] = fmaf(bfhi(w.y), s, a[3]);
    a[4] = fmaf(bflo(w.z), s, a[4]); a[5] = fmaf(bfhi(w.z), s, a[5]);
    a[6] = fmaf(bflo(w.w), s, a[6]); a[7] = fmaf(bfhi(w.w), s, a[7]);
}
template <int N, int M> __device__ __forceinline__ void halve(float* a, int lane) {
    const bool up = lane & M;
#pragma unroll
    for (int i = 0; i < N / 2; i++) {
        float keep = up ? a[i + N / 2] : a[i];
        float send = up ? a[i] : a[i + N / 2];
        a[i] = keep + __shfl_xor_sync(0xffffffffu, send, M);
    }
}
__device__ __forceinline__ void mma16816(float* c, uint32_t a0, uint32_t a1, uint32_t a2, uint32_t a3, uint32_t b0, uint32_t b1) {
    asm volatile("mma.sync.aligned.m16n8k16.row.col.f32.bf16.bf16.f32 {%0,%1,%2,%3}, {%4,%5,%6,%7}, {%8,%9}, {%0,%1,%2,%3};"
                 : "+f"(c[0]), "+f"(c[1]), "+f"(c[2]), "+f"(c[3]) : "r"(a0), "r"(a1), "r"(a2), "r"(a3), "r"(b0), "r"(b1));
}

__global__ void __cluster_dims__(8, 1, 1) __launch_bounds__(NTHREADS, 1)
fused_decode_kernel(const __grid_constant__ Params p, const __grid_constant__ CUtensorMap tq,
                    const __grid_constant__ CUtensorMap t1, const __grid_constant__ CUtensorMap t2,
                    const __grid_constant__ CUtensorMap tv, const __grid_constant__ CUtensorMap to) {
    extern __shared__ __align__(1024) char sm[];
    __shared__ __align__(8) uint64_t bars[NBAR];
    __shared__ __align__(16) float xn_s[D_MODEL];
    __shared__ __align__(16) float red_s[8][64];
    __shared__ __align__(128) uint32_t q_s[8][256];
    __shared__ __align__(16) float2 sc_s[512];
    __shared__ __align__(16) float2 ml_s[8][8];
    __shared__ __align__(16) float in_s[8][8][64];
    __shared__ float b1_s[40];
    __shared__ uint32_t ep_s, g0_s;

    uint32_t (*p_s)[256] = reinterpret_cast<uint32_t (*)[256]>(red_s);
    uint32_t* h_s = reinterpret_cast<uint32_t*>(sc_s);
    const int c = blockIdx.x;
    const uint32_t bar0 = s2u(bars), sm0 = s2u(sm);
    const int cl = c >> 3, r = c & 7;
    const bool strm = cl < 8;
    const int warp = __shfl_sync(0xffffffffu, threadIdx.x >> 5, 0);
    int lane;
    asm volatile("mov.u32 %0, %laneid;" : "=r"(lane));

    auto gather_o = [&](int h) {
        const int g = lane >> 2, tq4 = lane & 3;
        mbar_wait(bar0 + B_WGT * 8, 0);
        const uint32_t tag = (ep_s + 1) & 3u;
        const float wg = ml_s[h][g].x;
        const uint32_t due = p.to6 - (6 - h) * p.th;
        while (gtime() - *reinterpret_cast<volatile uint32_t*>(&g0_s) < due) __nanosleep(64);
        const uint32_t* src = &p.s->obox[h][r][g][tq4 * 4];
        uint4 ov[4];
        int it = 0;
        while (true) {
#pragma unroll
            for (int i = 0; i < 4; i++) ov[i] = ldg_poll(src + i * 16);
            const uint32_t bad = (bad4(ov[3], tag) | bad4(ov[2], tag)) | (bad4(ov[1], tag) | bad4(ov[0], tag));
            if (!__any_sync(0xffffffffu, bad) || ++it >= SPIN_LIMIT) break;
            __nanosleep(100);
        }
        float a[16];
#pragma unroll
        for (int i = 0; i < 4; i++) {
            a[4 * i] = __uint_as_float(ov[i].x) * wg; a[4 * i + 1] = __uint_as_float(ov[i].y) * wg;
            a[4 * i + 2] = __uint_as_float(ov[i].z) * wg; a[4 * i + 3] = __uint_as_float(ov[i].w) * wg;
        }
        halve<16, 16>(a, lane); halve<8, 8>(a, lane); halve<4, 4>(a, lane);
        h_s[(7 + 2 * h + (g >> 2)) * 16 + tq4 * 4 + (g & 3)] = pack_bf(a[0], a[1]);
        __syncwarp();
        if (lane == 0) mbar_arrive(bar0 + (h == 6 ? B_O6 : B_O05) * 8, h == 6 ? 8 : h < 2 ? 2 : 1);
    };

    if (warp == 0) {
        uint32_t g0 = 0;
        uint64_t pol;
        asm volatile("createpolicy.fractional.L2::evict_first.b64 %0, 1.0;" : "=l"(pol));
        const int row0 = SK - WKEYS + c * 32;
        if (elect()) {
#pragma unroll
            for (int i = 0; i <= IT_K; i++) mbar_init(bar0 + i * 8, 1);
            mbar_fence_init();
            if (strm) {
                mbar_expect(bar0 + IT_K * 8, TILE);
                bulk(sm0 + IT_K * TILE, p.k + (size_t)row0 * 512, TILE, bar0 + IT_K * 8, pol);
#pragma unroll
                for (int i = 0; i < 4; i++) { mbar_expect(bar0 + i * 8, TILE); tma2d(sm0 + i * TILE, &tq, c * 64, i * 128, bar0 + i * 8); }
            }
            g0 = gtime();
            g0_s = g0;
        }
        __syncwarp();
        bar_arrive<1, NTHREADS>();
        bar_sync<2, 64>();
        cluster_arrive();
        if (elect()) {
            if (strm) {
                asm volatile("prefetch.tensormap [%0];" :: "l"(&tv) : "memory");
                uint32_t target = p.t0 * 16;
                int slot = IT_K + 1, ph = 1;
#pragma unroll 1
                for (int it = IT_K + 1; it < NIT; it++) {
                    mbar_wait(bar0 + (B_EMPTY + slot) * 8, ph);
                    while ((gtime() - g0) * 16 < target) { }
                    target += p.pace;
                    const uint32_t b = bar0 + (B_FULL + it) * 8, dst = sm0 + slot * TILE;
                    const int tt = (it - IT_K) & 15, row = row0 + (tt >> 1) * SK + (tt & 1) * 2048;
                    mbar_expect(b, TILE);
                    if (it < IT_V) bulk(dst, p.k + (size_t)row * 512, TILE, b, pol);
                    else tma4d(dst, &tv, row >> 3, b, pol);
                    if (++slot == NS) { slot = 0; ph ^= 1; }
                }
            } else {
                const int k = cl - 8;
                while (gtime() - g0 < p.tw1) { }
                mbar_expect(bar0, 28672);
                tma2d(sm0, &t1, (c - 64) * 32, 0, bar0);
                tma2d(sm0 + 14336, &t1, (c - 64) * 32, 224, bar0);
                asm volatile("prefetch.tensormap [%0];" :: "l"(&t2) : "memory");
                while (gtime() - g0 < p.two7) __nanosleep(200);
                mbar_expect(bar0 + 15 * 8, 8192);
                tma2d(sm0 + SM_WO + 7 * 8192, &to, k * 64, 7 * 512 + r * 64, bar0 + 15 * 8);
                mbar_wait(bar0 + B_TIME * 8, 0);
                g0 = g0_s;
                while (gtime() - g0 + 400 < p.tw2) __nanosleep(100);
                uint32_t target = p.tw2 * 16;
#pragma unroll 1
                for (int i = 0; i < 14; i++) {
                    while ((gtime() - g0) * 16 < target) { }
                    const uint32_t b = bar0 + (1 + i) * 8;
                    if (i < 7) {
                        target += p.pace_w2;
                        mbar_expect(b, 4096);
                        tma2d(sm0 + SM_W2 + i * 4096, &t2, k * 64, i * 256 + r * 32, b);
                    } else {
                        target += p.pace_wo;
                        mbar_expect(b, 8192);
                        tma2d(sm0 + SM_WO + (i - 7) * 8192, &to, k * 64, (i - 7) * 512 + r * 64, b);
                    }
                }
            }
        }
    } else if (warp <= 8) {
        const int w = warp - 1, t = threadIdx.x - 32;
        const int g = lane >> 2, tq4 = lane & 3;
        {
            uint32_t* xs = reinterpret_cast<uint32_t*>(sc_s);
            const uint32_t xm = w < 7 ? __ldg(reinterpret_cast<const uint32_t*>(p.x) + t) : 0u;
            xs[t] = xm;
            bar_sync<3, 256>();
            uint32_t xr[7];
#pragma unroll
            for (int i = 0; i < 7; i++) xr[i] = xs[lane + 32 * i];
            float sum = 0.f;
#pragma unroll
            for (int i = 0; i < 7; i++) sum += bflo(xr[i]) + bfhi(xr[i]);
#pragma unroll
            for (int o = 16; o; o >>= 1) sum += __shfl_xor_sync(0xffffffffu, sum, o);
            const float mean = sum * (1.f / D_MODEL);
            float var = 0.f;
#pragma unroll
            for (int i = 0; i < 7; i++) { float a = bflo(xr[i]) - mean, b = bfhi(xr[i]) - mean; var += a * a + b * b; }
#pragma unroll
            for (int o = 16; o; o >>= 1) var += __shfl_xor_sync(0xffffffffu, var, o);
            const float mb = rbf(mean);
            const float den = rbf(__fsqrt_rn(rbf(rbf(var * (1.f / D_MODEL)) + 1e-5f)));
            if (w < 7) {
                float2 v;
                v.x = rbf(__fdiv_rn(rbf(bflo(xm) - mb), den));
                v.y = rbf(__fdiv_rn(rbf(bfhi(xm) - mb), den));
                *reinterpret_cast<float2*>(&xn_s[2 * t]) = v;
            }
        }
        bar_sync<1, NTHREADS>();
        cluster_arrive();
        const uint32_t tag = (ep_s + 1) & 3u;

        if (strm) {
            if (w == 0) stg_pub2(&p.s->qbox[cl][r * 64 + 2 * lane], tag ^ 2u, tag ^ 2u);
            {
                float a[8];
#pragma unroll
                for (int i = 0; i < 8; i++) a[i] = 0.f;
#pragma unroll 1
                for (int b = 0; b < 4; b++) {
                    mbar_wait(bar0 + (B_FULL + b) * 8, 0);
                    const uint32_t base = sm0 + b * TILE + t * 16;
                    const float* xs = &xn_s[b * 128 + (t >> 3)];
                    fma8(a, lds128(base), xs[0]);
                    fma8(a, lds128(base + 4096), xs[32]);
                    if (b < 3) {
                        fma8(a, lds128(base + 8192), xs[64]);
                        fma8(a, lds128(base + 12288), xs[96]);
                    }
                    __syncwarp();
                    if (lane == 0) mbar_arrive(bar0 + (B_EMPTY + b) * 8, 1);
                }
                halve<8, 16>(a, lane); halve<4, 8>(a, lane);
                *reinterpret_cast<float2*>(&red_s[w][(lane & 7) * 8 + (lane >> 3) * 2]) = make_float2(a[0], a[1]);
                bar_sync<3, 256>();
                if (w == 0) {
                    float q0 = 0.f, q1 = 0.f;
#pragma unroll
                    for (int i = 0; i < 8; i++) { const float2 v = *reinterpret_cast<const float2*>(&red_s[i][2 * lane]); q0 += v.x; q1 += v.y; }
                    stg_pub2(&p.s->qbox[cl][r * 64 + 2 * lane], __float_as_uint(rbf(q0)) | tag, __float_as_uint(rbf(q1)) | tag);
                }
            }
            mbar_wait(bar0 + B_Q * 8, 0);
            const uint32_t qa0 = s2u(&q_s[0][0]) + (g & 1) * 512 + tq4 * 16 + (((g >> 1) ^ g) & 1) * 64, qa1 = qa0 ^ 64;
            const uint32_t ka0 = sm0 + (w & 1) * 8192 + g * 512 + tq4 * 16 + (g & 1) * 64;
            const uint32_t sa = s2u(&sc_s[(w & 1) * 16 + g]);
#pragma unroll 1
            for (int i4 = 0; i4 < 4; i4++) {
                const int tile = (w >> 1) + 4 * i4, it = IT_K + tile;
                const int slot = it >= NS ? it - NS : it;
                uint4 qf[8];
#pragma unroll
                for (int i = 0; i < 8; i++) qf[i] = lds128((i & 1 ? qa1 : qa0) + (tile >> 1) * 1024 + (i >> 1) * 128);
                mbar_wait(bar0 + (B_FULL + it) * 8, 0);
                float ca[4] = {0.f, 0.f, 0.f, 0.f}, cb[4] = {0.f, 0.f, 0.f, 0.f};
                const uint32_t base0 = ka0 + slot * TILE, base1 = base0 ^ 64;
#pragma unroll
                for (int i = 0; i < 8; i++) {
                    const uint32_t a = (i & 1 ? base1 : base0) + (i >> 1) * 128;
                    const uint4 lo = lds128(a), hi = lds128(a + 4096);
                    mma16816(ca, lo.x, hi.x, lo.y, hi.y, qf[i].x, qf[i].y);
                    mma16816(cb, lo.z, hi.z, lo.w, hi.w, qf[i].z, qf[i].w);
                }
                if (lane == 0) mbar_arrive(bar0 + (B_EMPTY + slot) * 8, 4);
                if (tq4 == (g & 1)) {
                    const uint32_t s0 = pack_bf(ca[0] + cb[0], ca[1] + cb[1]), s1 = pack_bf(ca[2] + cb[2], ca[3] + cb[3]);
                    sts64f(sa + tile * 256, bflo(s0) * 0.0625f, bfhi(s0) * 0.0625f);
                    sts64f(sa + tile * 256 + 64, bflo(s1) * 0.0625f, bfhi(s1) * 0.0625f);
                }
            }
            bar_sync<3, 256>();
            {
                float4 s = *reinterpret_cast<const float4*>(&sc_s[2 * t]);
                float m0 = fmaxf(s.x, s.z), m1 = fmaxf(s.y, s.w);
#pragma unroll
                for (int o = 16; o; o >>= 1) { m0 = fmaxf(m0, __shfl_xor_sync(0xffffffffu, m0, o)); m1 = fmaxf(m1, __shfl_xor_sync(0xffffffffu, m1, o)); }
                s.x = exp2f((s.x - m0) * LOG2E); s.y = exp2f((s.y - m1) * LOG2E);
                s.z = exp2f((s.z - m0) * LOG2E); s.w = exp2f((s.w - m1) * LOG2E);
                const int pos = (t & ~15) + (t & 3) * 4 + ((t >> 2) & 3);
                p_s[0][pos] = pack_bf(s.x, s.z);
                p_s[1][pos] = pack_bf(s.y, s.w);
                float l0 = s.x + s.z, l1 = s.y + s.w;
#pragma unroll
                for (int o = 16; o; o >>= 1) { l0 += __shfl_xor_sync(0xffffffffu, l0, o); l1 += __shfl_xor_sync(0xffffffffu, l1, o); }
                cluster_wait();
                if (lane < 8) st_async2(mapa(s2u(&ml_s[w][r]), lane), __float_as_uint(lane < 4 ? m0 : m1), __float_as_uint(lane < 4 ? l0 : l1), mapa(bar0 + B_ML * 8, lane));
                bar_sync<3, 256>();
            }
            {
                const uint32_t lo = sm0 + (w >> 1) * 1024 + (lane & 7) * 128 + (lane >> 4) * 4096;
                const uint32_t sw = ((w & 1) * 4 + ((lane >> 3) & 1)) ^ (lane & 7);
                const uint32_t pa = s2u(&p_s[g & 1][tq4 * 4]);
                const int dst = (tq4 & 1) * 4 + (w >> 1);
                const uint32_t da = mapa(s2u(&in_s[0][r][(w & 1) * 32 + (tq4 >> 1) * 16 + g]), dst), db = mapa(bar0 + B_O * 8, dst);
                int slot = IT_V - NS;
#pragma unroll 1
                for (int h = 0; h < 8; h++) {
                    float acc[4][4];
#pragma unroll
                    for (int i = 0; i < 4; i++) { acc[i][0] = acc[i][1] = acc[i][2] = acc[i][3] = 0.f; }
#pragma unroll
                    for (int j = 0; j < 2; j++) {
                        const uint4 pf = lds128(pa + (2 * h + j) * 64);
                        const uint32_t base = lo + (slot + j) * TILE;
                        mbar_wait(bar0 + (B_FULL + IT_V + 2 * h + j) * 8, 0);
                        uint4 vf[4];
#pragma unroll
                        for (int i = 0; i < 4; i++) vf[i] = ldsm4t(base + (i >> 1) * 8192 + ((sw ^ (2 * (i & 1))) << 4));
                        mma16816(acc[0], vf[0].x, vf[0].y, vf[0].z, vf[0].w, pf.x, pf.y);
                        mma16816(acc[1], vf[1].x, vf[1].y, vf[1].z, vf[1].w, pf.x, pf.y);
                        mma16816(acc[2], vf[2].x, vf[2].y, vf[2].z, vf[2].w, pf.z, pf.w);
                        mma16816(acc[3], vf[3].x, vf[3].y, vf[3].z, vf[3].w, pf.z, pf.w);
                        if (lane == 0) mbar_arrive(bar0 + (B_EMPTY + slot + j) * 8, 1);
                    }
                    slot += 2;
                    if (slot == NS) slot = 0;
                    const bool hi = tq4 & 2, h1 = tq4 & 1;
                    const float x0 = hi ? acc[1][0] + acc[3][0] : acc[0][0] + acc[2][0], x1 = hi ? acc[1][1] + acc[3][1] : acc[0][1] + acc[2][1];
                    const float x2 = hi ? acc[1][2] + acc[3][2] : acc[0][2] + acc[2][2], x3 = hi ? acc[1][3] + acc[3][3] : acc[0][3] + acc[2][3];
                    st_async1(da + h * 2048, __float_as_uint(h1 ? x1 : x0), db + h * 8);
                    st_async1(da + h * 2048 + 32, __float_as_uint(h1 ? x3 : x2), db + h * 8);
                }
            }
        } else {
            const int k = cl - 8;
            if (w == 0) stg_pub1(&p.s->hbox[r][k * 32 + lane], tag ^ 2u);
            {
                float a[8];
#pragma unroll
                for (int i = 0; i < 8; i++) a[i] = 0.f;
                mbar_wait(bar0, 0);
#pragma unroll 1
                for (int i = 0; i < 7; i++) fma8(a, lds128(sm0 + (t + 256 * i) * 16), xn_s[(t >> 2) + 64 * i]);
                halve<8, 16>(a, lane); halve<4, 8>(a, lane); halve<2, 4>(a, lane);
                red_s[w][(lane & 3) * 8 + (lane >> 2)] = a[0];
                bar_sync<3, 256>();
                if (w == 0) {
                    float h = 0.f;
#pragma unroll
                    for (int i = 0; i < 8; i++) h += red_s[i][lane];
                    h = rbf(rbf(h) + b1_s[lane]);
                    const float u = 0.7978845608028654f * (h + 0.044715f * h * h * h);
                    stg_pub1(&p.s->hbox[r][k * 32 + lane], __float_as_uint(rbf(0.5f * h * (1.f + tanhf(u)))) | tag);
                }
                if (t < 56) {
                    uint4 v;
                    int it = 0;
                    do { __nanosleep(1000); v = ldg_poll(&p.s->hbox[r][t * 4]); } while (bad4(v, tag) && ++it < SPIN_LIMIT);
                    const int pi = 2 * t, pos = (pi & ~15) + (pi & 3) * 4 + ((pi >> 2) & 3);
                    h_s[pos] = __byte_perm(v.x, v.y, 0x7632);
                    h_s[pos + 4] = __byte_perm(v.z, v.w, 0x7632);
                }
                bar_sync<3, 256>();
            }
            cluster_wait();
            if (w < 6) gather_o(w);
            {
                float acc[2][4] = {{0.f, 0.f, 0.f, 0.f}, {0.f, 0.f, 0.f, 0.f}};
                const uint32_t base = sm0 + SM_W2 + ((lane & 7) + 16 * ((lane >> 3) & 1) + 8 * (lane >> 4)) * 128 + ((w ^ (lane & 7)) << 4);
                const uint32_t va = s2u(&h_s[tq4 * 4 + (g & 1) * 2]);
                const uint32_t da = mapa(s2u(&in_s[0][0][(32 + r) * 8 + g]), w), db = mapa(bar0 + B_F * 8, w);
                uint4 u0, u1;
                float2 b0, b1;
#pragma unroll
                for (int i = 0; i < 15; i++) {
                    uint4 n0, n1;
                    float2 c0, c1;
                    if (i == 13) {
                        mma16816(acc[0], u0.x, u0.y, u0.z, u0.w, __float_as_uint(b0.x), __float_as_uint(b0.y));
                        mma16816(acc[1], u1.x, u1.y, u1.z, u1.w, __float_as_uint(b1.x), __float_as_uint(b1.y));
                    }
                    if (i < 14) {
                        if (i == 7 || i == 13) mbar_wait(bar0 + (i == 7 ? B_O05 : B_O6) * 8, 0);
                        const int j = i < 7 ? i : 2 * i - 7;
                        c0 = lds64f(va + j * 64);
                        if (i >= 7) c1 = lds64f(va + j * 64 + 64);
                        mbar_wait(bar0 + (1 + i) * 8, 0);
                        n0 = ldsm4t(base + (i < 7 ? j : j + 1) * 4096);
                        if (i >= 7) n1 = ldsm4t(base + (j + 2) * 4096);
                    }
                    if (i > 0 && i != 13) {
                        mma16816(acc[i > 7 ? 0 : i & 1], u0.x, u0.y, u0.z, u0.w, __float_as_uint(b0.x), __float_as_uint(b0.y));
                        if (i > 7) mma16816(acc[1], u1.x, u1.y, u1.z, u1.w, __float_as_uint(b1.x), __float_as_uint(b1.y));
                    }
                    u0 = n0; u1 = n1; b0 = c0; b1 = c1;
                }
                if (tq4 == 0) st_async1(da, __float_as_uint((acc[0][0] + acc[0][3]) + (acc[1][0] + acc[1][3])), db);
            }
        }
    } else {
        const int fw = warp - 9, t = threadIdx.x - 288;
        if (fw == 0) {
            if (elect()) {
#pragma unroll
                for (int i = IT_K + 1; i < NBAR; i++) mbar_init(bar0 + i * 8, (i >= B_EMPTY && i < B_Q) ? 8 : 1);
                mbar_fence_init();
            }
            __syncwarp();
            bar_arrive<2, 64>();
            if (elect()) {
                mbar_expect(bar0 + B_Q * 8, 8192);
                mbar_expect(bar0 + B_ML * 8, strm ? 512 : 1024);
                mbar_expect(bar0 + B_F * 8, 256);
#pragma unroll
                for (int i = 0; i < 8; i++) mbar_expect(bar0 + (B_O + i) * 8, 2048);
            }
            __syncwarp();
        } else if (fw == 1) {
            uint32_t e;
            asm volatile("ld.relaxed.gpu.global.u32 %0, [%1];" : "=r"(e) : "l"(&p.s->epoch) : "memory");
            if (lane == 0) ep_s = e;
        } else if (!strm) {
            if (fw == 2) {
                b1_s[lane] = __bfloat162float(p.b1[(c - 64) * 32 + lane]);
            } else if (fw == 3) {
                const int col = (c - 64) * 8 + (lane & 7);
                if (lane < 8) b1_s[32 + lane] = __bfloat162float(p.x[col]) + __bfloat162float(p.b2[col]);
            }
        }
        bar_sync<1, NTHREADS>();
        cluster_arrive();
        const uint32_t tag = (ep_s + 1) & 3u;
        if (fw == 4) {
            if (!strm) {
                const uint32_t g0 = g0_s;
                while (gtime() - g0 < p.tt) __nanosleep(200);
                uint32_t v;
                int it = 0;
                while (true) {
                    asm volatile("ld.relaxed.gpu.global.u32 %0, [%1];" : "=r"(v) : "l"(&p.s->tbox[r][lane & 7][0]) : "memory");
                    if (!__any_sync(0xffffffffu, (v ^ tag) & 3u) || ++it >= SPIN_LIMIT) break;
                    __nanosleep(100);
                }
                int sum = (int)(v - g0 - p.tn);
#pragma unroll
                for (int o = 1; o < 8; o <<= 1) sum += __shfl_xor_sync(0xffffffffu, sum, o);
                if (lane == 0) {
                    *reinterpret_cast<volatile uint32_t*>(&g0_s) = g0 + ((min(max(sum, -8 * 800), 8 * 4000) * 5) >> 5);
                    mbar_arrive(bar0 + B_TIME * 8, 1);
                }
                __syncwarp();
                gather_o(6);
            }
        } else if (strm) {
            {
                uint4 v;
                int it = 0;
                mbar_wait(bar0 + (B_EMPTY + 3) * 8, 0);
                while (true) {
                    __nanosleep(it ? 150 : 500);
                    v = ldg_poll(&p.s->qbox[r][t * 4]);
                    if (!bad4(v, tag) || ++it >= SPIN_LIMIT) break;
                }
                __syncwarp();
                cluster_wait();
                const uint32_t lo = __byte_perm(v.x, v.y, 0x7632), hi = __byte_perm(v.z, v.w, 0x7632);
#pragma unroll
                for (int d = 0; d < 8; d++) st_async2(mapa(s2u(&q_s[r][(t * 2) ^ ((t >> 6) * 16)]), d), lo, hi, mapa(bar0 + B_Q * 8, d));
            }
            if (fw == 0) {
                uint32_t* dst = &p.s->obox[0][r][cl][(lane >> 3) * 16 + (lane & 3) * 4 + ((lane >> 2) & 1) * 2];
#pragma unroll
                for (int h = 0; h < 8; h++) stg_pub2(dst + h * 4096, tag ^ 2u, tag ^ 2u);
                if ((lane & 7) == 0) { stg_pub2(&p.s->sbox[r][cl][2 * (lane >> 3)], tag ^ 2u, tag ^ 2u); stg_pub2(&p.s->sbox[r][cl][2 * (lane >> 3) + 8], tag ^ 2u, tag ^ 2u); }
                if (lane < 8) stg_pub1(&p.s->tbox[r][cl][lane], tag ^ 2u);
                mbar_wait(bar0 + B_ML * 8, 0);
                float e[2];
#pragma unroll
                for (int i = 0; i < 2; i++) {
                    const float2 v = ml_s[(lane >> 3) + 4 * i][lane & 7];
                    float M = v.x;
#pragma unroll
                    for (int o = 1; o < 8; o <<= 1) M = fmaxf(M, __shfl_xor_sync(0xffffffffu, M, o));
                    e[i] = exp2f((v.x - M) * LOG2E);
                    float L = v.y * e[i];
#pragma unroll
                    for (int o = 1; o < 8; o <<= 1) L += __shfl_xor_sync(0xffffffffu, L, o);
                    if ((lane & 7) == 0) stg_pub2(&p.s->sbox[r][cl][2 * ((lane >> 3) + 4 * i)], tagf(M, tag), tagf(L, tag));
                }
#pragma unroll 1
                for (int h = 0; h < 8; h++) {
                    float ws[8];
#pragma unroll
                    for (int s = 0; s < 8; s++) ws[s] = __shfl_sync(0xffffffffu, h < 4 ? e[0] : e[1], (h & 3) * 8 + s);
                    mbar_wait(bar0 + (B_O + h) * 8, 0);
                    float2 ov[8];
#pragma unroll
                    for (int s = 0; s < 8; s++) ov[s] = lds64f(s2u(&in_s[h][s][2 * lane]));
                    const float o0 = (fmaf(ov[0].x, ws[0], ov[1].x * ws[1]) + fmaf(ov[2].x, ws[2], ov[3].x * ws[3])) + (fmaf(ov[4].x, ws[4], ov[5].x * ws[5]) + fmaf(ov[6].x, ws[6], ov[7].x * ws[7]));
                    const float o1 = (fmaf(ov[0].y, ws[0], ov[1].y * ws[1]) + fmaf(ov[2].y, ws[2], ov[3].y * ws[3])) + (fmaf(ov[4].y, ws[4], ov[5].y * ws[5]) + fmaf(ov[6].y, ws[6], ov[7].y * ws[7]));
                    stg_pub2(dst + h * 4096, tagf(o0, tag), tagf(o1, tag));
                    if (h == 1 && lane < 8) stg_pub1(&p.s->tbox[r][cl][lane], (gtime() & ~3u) | tag);
                }
            }
        } else {
            const int g = lane >> 2, tq4 = lane & 3;
            mbar_wait(bar0 + 15 * 8, 0);
            uint4 wf[4];
#pragma unroll
            for (int j = 0; j < 4; j++)
                wf[j] = ldsm4t(sm0 + SM_WO + 7 * 8192 + fw * 2048 + ((lane & 7) + 8 * (lane >> 4)) * 128 + (((2 * j + ((lane >> 3) & 1)) ^ (lane & 7)) << 4));
            float wgt[2];
            {
                uint4 v;
                int it = 0;
                while (true) {
                    v = ldg_poll(&p.s->sbox[r][g][4 * tq4]);
                    if (!__any_sync(0xffffffffu, bad4(v, tag)) || ++it >= SPIN_LIMIT) break;
                    __nanosleep(300);
                }
#pragma unroll
                for (int i = 0; i < 2; i++) {
                    const float m = __uint_as_float((i ? v.z : v.x) & ~3u);
                    float M = m;
#pragma unroll
                    for (int o = 4; o < 32; o <<= 1) M = fmaxf(M, __shfl_xor_sync(0xffffffffu, M, o));
                    const float e = exp2f((m - M) * LOG2E);
                    float L = __uint_as_float((i ? v.w : v.y) & ~3u) * e;
#pragma unroll
                    for (int o = 4; o < 32; o <<= 1) L += __shfl_xor_sync(0xffffffffu, L, o);
                    wgt[i] = __fdividef(e, L);
                }
                if (fw == 0) {
                    ml_s[2 * tq4][g].x = wgt[0]; ml_s[2 * tq4 + 1][g].x = wgt[1];
                    __syncwarp();
                    if (lane == 0) mbar_arrive(bar0 + B_WGT * 8, 1);
                }
            }
            const uint32_t fa = s2u(&in_s[0][0][(r * 4 + fw) * 8 + g]);
            const uint32_t da0 = mapa(fa, 2 * tq4), db0 = mapa(bar0 + B_F7 * 8, 2 * tq4), da1 = mapa(fa, 2 * tq4 + 1), db1 = mapa(bar0 + B_F7 * 8, 2 * tq4 + 1);
            const float wg7 = __shfl_sync(0xffffffffu, wgt[1], (lane & 28) + 3);
            cluster_wait();
            const uint32_t* src = &p.s->obox[7][r][g][fw * 16 + tq4 * 4];
            uint4 ov;
            {
                while (gtime() - *reinterpret_cast<volatile uint32_t*>(&g0_s) < p.to7) __nanosleep(64);
                int it = 0;
                do { ov = ldg_poll(src); } while (__any_sync(0xffffffffu, bad4(ov, tag)) && ++it < SPIN_LIMIT);
            }
            const uint32_t b0 = pack_bf(__uint_as_float(ov.x) * wg7, __uint_as_float(ov.y) * wg7), b1 = pack_bf(__uint_as_float(ov.z) * wg7, __uint_as_float(ov.w) * wg7);
            float a[8];
#pragma unroll
            for (int j = 0; j < 4; j++) {
                float acc[4] = {0.f, 0.f, 0.f, 0.f};
                mma16816(acc, wf[j].x, wf[j].y, wf[j].z, wf[j].w, b0, b1);
                a[2 * j] = acc[0] + acc[1]; a[2 * j + 1] = acc[2] + acc[3];
            }
            halve<8, 2>(a, lane); halve<4, 1>(a, lane);
            st_async1(da0, __float_as_uint(a[0]), db0);
            st_async1(da1, __float_as_uint(a[1]), db1);
            if (fw == 0) {
                const float base = b1_s[32 + (lane & 7)];
                __nv_bfloat16* dst = p.out + (c - 64) * 8 + (lane & 7);
                const volatile float* in = &in_s[0][0][0];
                float s[8];
                mbar_wait(bar0 + B_F7 * 8, 0);
#pragma unroll
                for (int i = 0; i < 8; i++) s[i] = in[i * 32 + lane];
                float v = ((s[0] + s[1]) + (s[2] + s[3])) + ((s[4] + s[5]) + (s[6] + s[7]));
                v += __shfl_xor_sync(0xffffffffu, v, 8);
                v += __shfl_xor_sync(0xffffffffu, v, 16);
                v += base;
                mbar_wait(bar0 + B_F * 8, 0);
#pragma unroll
                for (int i = 0; i < 8; i++) s[i] = in[256 + i * 8 + (lane & 7)];
                v += ((s[0] + s[1]) + (s[2] + s[3])) + ((s[4] + s[5]) + (s[6] + s[7]));
                if (lane < 8) *dst = __float2bfloat16_rn(v);
                if (c == 64 && lane == 0) p.s->epoch = ep_s + 1;
            }
        }
    }
}

typedef CUresult (*EncodeFn)(CUtensorMap*, CUtensorMapDataType, cuuint32_t, void*, const cuuint64_t*, const cuuint64_t*,
                             const cuuint32_t*, const cuuint32_t*, CUtensorMapInterleave, CUtensorMapSwizzle,
                             CUtensorMapL2promotion, CUtensorMapFloatOOBfill);

void make_map(EncodeFn encode, CUtensorMap* m, void* base, uint64_t cols, uint64_t rows, uint32_t bc, uint32_t br, bool swz) {
    cuuint64_t gd[2] = {cols, rows}; cuuint64_t gs[1] = {cols * 2}; cuuint32_t bd[2] = {bc, br}; cuuint32_t es[2] = {1, 1};
    encode(m, CU_TENSOR_MAP_DATA_TYPE_BFLOAT16, 2, base, gd, gs, bd, es, CU_TENSOR_MAP_INTERLEAVE_NONE,
           swz ? CU_TENSOR_MAP_SWIZZLE_128B : CU_TENSOR_MAP_SWIZZLE_NONE, CU_TENSOR_MAP_L2_PROMOTION_L2_128B, CU_TENSOR_MAP_FLOAT_OOB_FILL_NONE);
}

}

static const uint32_t g_cfg[12] = {5100, 1500, 500, 8800, 11850, 1300, 2450, 13100, 13500, 9650, 9270, 650};

extern "C" void kernel_launch(void* const* d_in, const int* in_sizes, int n_in, void* d_out, int out_size) {
    (void)in_sizes; (void)n_in; (void)out_size;
    static EncodeFn encode = nullptr;
    static Scratch* scratch = nullptr;
    static double f = 1.0;
    if (!encode) {
        void* fn = nullptr;
        cudaDriverEntryPointQueryResult st;
        cudaGetDriverEntryPoint("cuTensorMapEncodeTiled", &fn, cudaEnableDefault, &st);
        encode = (EncodeFn)fn;
        cudaGetSymbolAddress((void**)&scratch, g_scratch);
        int dev = 0, khz = 0, bits = 0;
        cudaGetDevice(&dev);
        cudaDeviceGetAttribute(&khz, cudaDevAttrMemoryClockRate, dev);
        cudaDeviceGetAttribute(&bits, cudaDevAttrGlobalMemoryBusWidth, dev);
        if (khz > 0 && bits > 0) f = (2619000.0 * 5120.0) / ((double)khz * bits);
        cudaFuncSetAttribute(fused_decode_kernel, cudaFuncAttributeMaxDynamicSharedMemorySize, SM_DYN);
    }
    CUtensorMap tq, t1, t2, tv, to;
    make_map(encode, &tq, d_in[3], 4096, D_MODEL, 64, 128, false);
    make_map(encode, &t1, d_in[6], FFN, D_MODEL, 32, 224, false);
    make_map(encode, &t2, d_in[8], D_MODEL, FFN, 64, 32, true);
    make_map(encode, &to, d_in[4], D_MODEL, 4096, 64, 64, true);
    {
        cuuint64_t gd[4] = {64, 8, 4, (cuuint64_t)SK}; cuuint64_t gs[3] = {512, 128, 4096}; cuuint32_t bd[4] = {64, 8, 4, 4}; cuuint32_t es[4] = {1, 1, 1, 1};
        encode(&tv, CU_TENSOR_MAP_DATA_TYPE_BFLOAT16, 4, d_in[2], gd, gs, bd, es, CU_TENSOR_MAP_INTERLEAVE_NONE,
               CU_TENSOR_MAP_SWIZZLE_128B, CU_TENSOR_MAP_L2_PROMOTION_NONE, CU_TENSOR_MAP_FLOAT_OOB_FILL_NONE);
    }
    Params p;
    p.x = (const __nv_bfloat16*)d_in[0];
    p.k = (const char*)d_in[1];
    p.b1 = (const __nv_bfloat16*)d_in[7];
    p.b2 = (const __nv_bfloat16*)d_in[9];
    p.out = (__nv_bfloat16*)d_out;
    p.s = scratch;
    auto sc = [&](int i, double fixed) { return (uint32_t)(fixed + (g_cfg[i] - fixed) * f + 0.5); };
    p.pace = sc(0, 0); p.t0 = sc(1, 0); p.tw1 = sc(2, 0); p.two7 = sc(3, 1000); p.tw2 = sc(4, 0); p.pace_w2 = sc(5, 0); p.pace_wo = sc(6, 0);
    p.to6 = sc(7, 1500); p.to7 = sc(8, 1300); p.tt = sc(9, 1400); p.tn = sc(10, 1000); p.th = sc(11, 0);
    fused_decode_kernel<<<NCTA, NTHREADS, SM_DYN, cudaStreamPerThread>>>(p, tq, t1, t2, tv, to);
}
```

```cpp
#include <cuda_runtime.h>
#include <cuda_bf16.h>
#include <cuda.h>
#include <stdint.h>

namespace {

constexpr int D_MODEL = 448;
constexpr int FFN = 1792;
constexpr int SK = 65536;
constexpr int WKEYS = 4096;
constexpr int NCTA = 120;
constexpr int TILE = 16384;
constexpr int NS = 12;
constexpr int NTHREADS = 32 * (1 + 8 + 5);
constexpr int SPIN_LIMIT = 1 << 20;
constexpr float LOG2E = 1.4426950408889634f;

constexpr int IT_K = 4, IT_V = 20, NIT = 36;
constexpr int B_FULL = 0, B_EMPTY = NIT, B_Q = NIT + NS, B_ML = B_Q + 1, B_F = B_Q + 2, B_O = B_Q + 3, NBAR = B_O + 8;
constexpr int B_WGT = 16, B_TIME = 17, B_O05 = B_EMPTY, B_O6 = B_EMPTY + 1, B_F7 = B_ML;
constexpr int SM_W2 = 2 * TILE, SM_WO = 4 * TILE;
constexpr int SM_DYN = NS * TILE;

struct Scratch {
    uint32_t qbox[8][512];
    uint32_t hbox[8][256];
    uint32_t sbox[8][8][16];
    uint32_t obox[8][8][8][64];
    uint32_t tbox[8][8][8];
    uint32_t epoch;
    uint32_t pad[31];
};
__device__ __align__(128) Scratch g_scratch;

struct Params {
    const __nv_bfloat16* x;
    const char* k;
    const __nv_bfloat16* b1;
    const __nv_bfloat16* b2;
    __nv_bfloat16* out;
    Scratch* s;
    uint32_t pace;
    uint32_t t0;
    uint32_t tw1;
    uint32_t ts;
    uint32_t tw2;
    uint32_t pace_w2;
    uint32_t pace_wo;
    uint32_t tt, tn;
    uint32_t th;
    uint32_t to6, to7;
};

__device__ __forceinline__ uint32_t s2u(const void* p) { return (uint32_t)__cvta_generic_to_shared(p); }
__device__ __forceinline__ void mbar_init(uint32_t b, uint32_t c) { asm volatile("mbarrier.init.shared::cta.b64 [%0], %1;" :: "r"(b), "r"(c) : "memory"); }
__device__ __forceinline__ void mbar_fence_init() { asm volatile("fence.mbarrier_init.release.cluster;" ::: "memory"); }
__device__ __forceinline__ void mbar_expect(uint32_t b, uint32_t bytes) { asm volatile("mbarrier.arrive.expect_tx.shared::cta.b64 _, [%0], %1;" :: "r"(b), "r"(bytes) : "memory"); }
__device__ __forceinline__ void mbar_arrive(uint32_t b, uint32_t n) { asm volatile("mbarrier.arrive.shared::cta.b64 _, [%0], %1;" :: "r"(b), "r"(n) : "memory"); }
__device__ __forceinline__ void mbar_wait(uint32_t b, uint32_t ph) {
    asm volatile("{\n.reg .pred p;\nW: mbarrier.try_wait.parity.shared::cta.b64 p, [%0], %1;\n@p bra D;\nbra W;\nD:\n}" :: "r"(b), "r"(ph) : "memory");
}
__device__ __forceinline__ void bulk(uint32_t dst, const void* src, uint32_t bytes, uint32_t bar, uint64_t pol) {
    asm volatile("cp.async.bulk.shared::cluster.global.mbarrier::complete_tx::bytes.L2::cache_hint [%0], [%1], %2, [%3], %4;" :: "r"(dst), "l"(src), "r"(bytes), "r"(bar), "l"(pol) : "memory");
}
__device__ __forceinline__ void tma2d(uint32_t dst, const void* tm, int x, int y, uint32_t bar) {
    asm volatile("cp.async.bulk.tensor.2d.shared::cluster.global.mbarrier::complete_tx::bytes [%0], [%1, {%3, %4}], [%2];" :: "r"(dst), "l"(tm), "r"(bar), "r"(x), "r"(y) : "memory");
}
__device__ __forceinline__ void tma4d(uint32_t dst, const void* tm, int y, uint32_t bar, uint64_t pol) {
    asm volatile("cp.async.bulk.tensor.4d.shared::cluster.global.mbarrier::complete_tx::bytes.L2::cache_hint [%0], [%1, {0, 0, 0, %3}], [%2], %4;" :: "r"(dst), "l"(tm), "r"(bar), "r"(y), "l"(pol) : "memory");
}
__device__ __forceinline__ uint4 ldsm4t(uint32_t a) { uint4 v; asm volatile("ldmatrix.sync.aligned.m8n8.x4.trans.shared.b16 {%0,%1,%2,%3}, [%4];" : "=r"(v.x), "=r"(v.y), "=r"(v.z), "=r"(v.w) : "r"(a)); return v; }
__device__ __forceinline__ uint32_t mapa(uint32_t a, uint32_t r) { uint32_t d; asm("mapa.shared::cluster.u32 %0, %1, %2;" : "=r"(d) : "r"(a), "r"(r)); return d; }
__device__ __forceinline__ void st_async1(uint32_t a, uint32_t x, uint32_t bar) {
    asm volatile("st.async.weak.shared::cluster.mbarrier::complete_tx::bytes.b32 [%0], %1, [%2];" :: "r"(a), "r"(x), "r"(bar) : "memory");
}
__device__ __forceinline__ void st_async2(uint32_t a, uint32_t x, uint32_t y, uint32_t bar) {
    asm volatile("st.async.weak.shared::cluster.mbarrier::complete_tx::bytes.v2.b32 [%0], {%1, %2}, [%3];" :: "r"(a), "r"(x), "r"(y), "r"(bar) : "memory");
}
__device__ __forceinline__ void cluster_arrive() { asm volatile("barrier.cluster.arrive.relaxed.aligned;" ::: "memory"); }
__device__ __forceinline__ void cluster_wait() { asm volatile("barrier.cluster.wait.aligned;" ::: "memory"); }
__device__ __forceinline__ bool elect() { uint32_t r; asm volatile("{\n.reg .pred p;\nelect.sync _|p, 0xffffffff;\nselp.u32 %0,1,0,p;\n}" : "=r"(r)); return r; }
__device__ __forceinline__ uint32_t gtime() { uint32_t t; asm volatile("mov.u32 %0, %globaltimer_lo;" : "=r"(t) :: "memory"); return t; }
template <int ID, int N> __device__ __forceinline__ void bar_sync() { asm volatile("bar.sync %0, %1;" :: "n"(ID), "n"(N) : "memory"); }
template <int ID, int N> __device__ __forceinline__ void bar_arrive() { asm volatile("bar.arrive %0, %1;" :: "n"(ID), "n"(N) : "memory"); }
__device__ __forceinline__ uint4 lds128(uint32_t a) { uint4 v; asm volatile("ld.shared.v4.u32 {%0,%1,%2,%3}, [%4];" : "=r"(v.x), "=r"(v.y), "=r"(v.z), "=r"(v.w) : "r"(a)); return v; }
__device__ __forceinline__ float2 lds64f(uint32_t a) { float2 v; asm volatile("ld.shared.v2.f32 {%0,%1}, [%2];" : "=f"(v.x), "=f"(v.y) : "r"(a)); return v; }
__device__ __forceinline__ void sts64f(uint32_t a, float x, float y) { asm volatile("st.shared.v2.f32 [%0], {%1,%2};" :: "r"(a), "f"(x), "f"(y) : "memory"); }
__device__ __forceinline__ uint4 ldg_poll(const void* p) { uint4 v; asm volatile("ld.relaxed.gpu.global.v4.u32 {%0,%1,%2,%3}, [%4];" : "=r"(v.x), "=r"(v.y), "=r"(v.z), "=r"(v.w) : "l"(p) : "memory"); return v; }
__device__ __forceinline__ void stg_pub2(void* p, uint32_t a, uint32_t b) { asm volatile("st.relaxed.gpu.global.v2.u32 [%0], {%1,%2};" :: "l"(p), "r"(a), "r"(b) : "memory"); }
__device__ __forceinline__ void stg_pub1(void* p, uint32_t a) { asm volatile("st.relaxed.gpu.global.u32 [%0], %1;" :: "l"(p), "r"(a) : "memory"); }
__device__ __forceinline__ uint32_t bad4(uint4 v, uint32_t tag) { return ((v.x ^ tag) | (v.y ^ tag) | (v.z ^ tag) | (v.w ^ tag)) & 3u; }
__device__ __forceinline__ uint32_t tagf(float f, uint32_t tag) { return (__float_as_uint(f) & ~3u) | tag; }
__device__ __forceinline__ float bflo(uint32_t u) { return __uint_as_float(u << 16); }
__device__ __forceinline__ float bfhi(uint32_t u) { return __uint_as_float(u & 0xffff0000u); }
__device__ __forceinline__ float rbf(float f) { return __bfloat162float(__float2bfloat16_rn(f)); }
__device__ __forceinline__ uint32_t pack_bf(float lo, float hi) { const __nv_bfloat162 r = __floats2bfloat162_rn(lo, hi); return *reinterpret_cast<const uint32_t*>(&r); }
__device__ __forceinline__ void fma8(float* a, uint4 w, float s) {
    a[0] = fmaf(bflo(w.x), s, a[0]); a[1] = fmaf(bfhi(w.x), s, a[1]);
    a[2] = fmaf(bflo(w.y), s, a[2]); a[3] = fmaf(bfhi(w.y), s, a[3]);
    a[4] = fmaf(bflo(w.z), s, a[4]); a[5] = fmaf(bfhi(w.z), s, a[5]);
    a[6] = fmaf(bflo(w.w), s, a[6]); a[7] = fmaf(bfhi(w.w), s, a[7]);
}
template <int N, int M> __device__ __forceinline__ void halve(float* a, int lane) {
    const bool up = lane & M;
#pragma unroll
    for (int i = 0; i < N / 2; i++) {
        float keep = up ? a[i + N / 2] : a[i];
        float send = up ? a[i] : a[i + N / 2];
        a[i] = keep + __shfl_xor_sync(0xffffffffu, send, M);
    }
}
__device__ __forceinline__ void mma16816(float* c, uint32_t a0, uint32_t a1, uint32_t a2, uint32_t a3, uint32_t b0, uint32_t b1) {
    asm volatile("mma.sync.aligned.m16n8k16.row.col.f32.bf16.bf16.f32 {%0,%1,%2,%3}, {%4,%5,%6,%7}, {%8,%9}, {%0,%1,%2,%3};"
                 : "+f"(c[0]), "+f"(c[1]), "+f"(c[2]), "+f"(c[3]) : "r"(a0), "r"(a1), "r"(a2), "r"(a3), "r"(b0), "r"(b1));
}

__global__ void __cluster_dims__(8, 1, 1) __launch_bounds__(NTHREADS, 1)
fused_decode_kernel(const __grid_constant__ Params p, const __grid_constant__ CUtensorMap tq,
                    const __grid_constant__ CUtensorMap t1, const __grid_constant__ CUtensorMap t2,
                    const __grid_constant__ CUtensorMap tv, const __grid_constant__ CUtensorMap to) {
    extern __shared__ __align__(1024) char sm[];
    __shared__ __align__(8) uint64_t bars[NBAR];
    __shared__ __align__(16) float xn_s[D_MODEL];
    __shared__ __align__(16) float red_s[8][64];
    __shared__ __align__(128) uint32_t q_s[8][256];
    __shared__ __align__(16) float2 sc_s[512];
    __shared__ __align__(16) float2 ml_s[8][8];
    __shared__ __align__(16) float in_s[8][8][64];
    __shared__ float b1_s[40];
    __shared__ uint32_t ep_s, g0_s;

    uint32_t (*p_s)[256] = reinterpret_cast<uint32_t (*)[256]>(red_s);
    uint32_t* h_s = reinterpret_cast<uint32_t*>(sc_s);
    const int c = blockIdx.x;
    const uint32_t bar0 = s2u(bars), sm0 = s2u(sm);
    const int cl = c >> 3, r = c & 7;
    const bool strm = cl < 8;
    const int warp = __shfl_sync(0xffffffffu, threadIdx.x >> 5, 0);
    int lane;
    asm volatile("mov.u32 %0, %laneid;" : "=r"(lane));

    auto gather_o = [&](int h) {
        const int g = lane >> 2, tq4 = lane & 3;
        mbar_wait(bar0 + B_WGT * 8, 0);
        const uint32_t tag = (ep_s + 1) & 3u;
        const float wg = ml_s[h][g].x;
        const uint32_t due = p.to6 - (6 - h) * p.th;
        while (gtime() - *reinterpret_cast<volatile uint32_t*>(&g0_s) < due) __nanosleep(64);
        const uint32_t* src = &p.s->obox[h][r][g][tq4 * 4];
        uint4 ov[4];
        int it = 0;
        while (true) {
#pragma unroll
            for (int i = 0; i < 4; i++) ov[i] = ldg_poll(src + i * 16);
            const uint32_t bad = (bad4(ov[3], tag) | bad4(ov[2], tag)) | (bad4(ov[1], tag) | bad4(ov[0], tag));
            if (!__any_sync(0xffffffffu, bad) || ++it >= SPIN_LIMIT) break;
            __nanosleep(100);
        }
        float a[16];
#pragma unroll
        for (int i = 0; i < 4; i++) {
            a[4 * i] = __uint_as_float(ov[i].x) * wg; a[4 * i + 1] = __uint_as_float(ov[i].y) * wg;
            a[4 * i + 2] = __uint_as_float(ov[i].z) * wg; a[4 * i + 3] = __uint_as_float(ov[i].w) * wg;
        }
        halve<16, 16>(a, lane); halve<8, 8>(a, lane); halve<4, 4>(a, lane);
        h_s[(7 + 2 * h + (g >> 2)) * 16 + tq4 * 4 + (g & 3)] = pack_bf(a[0], a[1]);
        __syncwarp();
        if (lane == 0) mbar_arrive(bar0 + (h == 6 ? B_O6 : B_O05) * 8, h == 6 ? 8 : h < 2 ? 2 : 1);
    };

    if (warp == 0) {
        uint32_t g0 = 0;
        uint64_t pol;
        asm volatile("createpolicy.fractional.L2::evict_first.b64 %0, 1.0;" : "=l"(pol));
        const int row0 = SK - WKEYS + c * 32;
        if (elect()) {
#pragma unroll
            for (int i = 0; i <= IT_K; i++) mbar_init(bar0 + i * 8, 1);
            mbar_fence_init();
            if (strm) {
                mbar_expect(bar0 + IT_K * 8, TILE);
                bulk(sm0 + IT_K * TILE, p.k + (size_t)row0 * 512, TILE, bar0 + IT_K * 8, pol);
#pragma unroll
                for (int i = 0; i < 4; i++) { mbar_expect(bar0 + i * 8, TILE); tma2d(sm0 + i * TILE, &tq, c * 64, i * 128, bar0 + i * 8); }
            }
            g0 = gtime();
            g0_s = g0;
        }
        __syncwarp();
        bar_arrive<1, NTHREADS>();
        bar_sync<2, 64>();
        cluster_arrive();
        if (elect()) {
            if (strm) {
                asm volatile("prefetch.tensormap [%0];" :: "l"(&tv) : "memory");
                uint32_t target = p.t0 * 16;
                int slot = IT_K + 1, ph = 1;
#pragma unroll 1
                for (int it = IT_K + 1; it < NIT; it++) {
                    mbar_wait(bar0 + (B_EMPTY + slot) * 8, ph);
                    while ((gtime() - g0) * 16 < target) { }
                    target += p.pace;
                    const uint32_t b = bar0 + (B_FULL + it) * 8, dst = sm0 + slot * TILE;
                    const int tt = (it - IT_K) & 15, row = row0 + (tt >> 1) * SK + (tt & 1) * 2048;
                    mbar_expect(b, TILE);
                    if (it < IT_V) bulk(dst, p.k + (size_t)row * 512, TILE, b, pol);
                    else tma4d(dst, &tv, row >> 3, b, pol);
                    if (++slot == NS) { slot = 0; ph ^= 1; }
                }
            } else {
                const int k = cl - 8;
                while (gtime() - g0 < p.tw1) { }
                mbar_expect(bar0, 28672);
                tma2d(sm0, &t1, (c - 64) * 32, 0, bar0);
                tma2d(sm0 + 14336, &t1, (c - 64) * 32, 224, bar0);
                asm volatile("prefetch.tensormap [%0];" :: "l"(&t2) : "memory");
                asm volatile("prefetch.tensormap [%0];" :: "l"(&to) : "memory");
                mbar_wait(bar0 + B_TIME * 8, 0);
                g0 = g0_s;
                while (gtime() - g0 + 400 < p.tw2) __nanosleep(100);
                uint32_t target = p.tw2 * 16;
                while ((gtime() - g0) * 16 < target) { }
                mbar_expect(bar0 + 15 * 8, 8192);
                tma2d(sm0 + SM_WO + 7 * 8192, &to, k * 64, 7 * 512 + r * 64, bar0 + 15 * 8);
                target += p.pace_wo;
#pragma unroll 1
                for (int i = 0; i < 14; i++) {
                    while ((gtime() - g0) * 16 < target) { }
                    const uint32_t b = bar0 + (1 + i) * 8;
                    if (i < 7) {
                        target += p.pace_w2;
                        mbar_expect(b, 4096);
                        tma2d(sm0 + SM_W2 + i * 4096, &t2, k * 64, i * 256 + r * 32, b);
                    } else {
                        target += p.pace_wo;
                        mbar_expect(b, 8192);
                        tma2d(sm0 + SM_WO + (i - 7) * 8192, &to, k * 64, (i - 7) * 512 + r * 64, b);
                    }
                }
            }
        }
    } else if (warp <= 8) {
        const int w = warp - 1, t = threadIdx.x - 32;
        const int g = lane >> 2, tq4 = lane & 3;
        {
            uint32_t* xs = reinterpret_cast<uint32_t*>(sc_s);
            const uint32_t xm = w < 7 ? __ldg(reinterpret_cast<const uint32_t*>(p.x) + t) : 0u;
            xs[t] = xm;
            bar_sync<3, 256>();
            uint32_t xr[7];
#pragma unroll
            for (int i = 0; i < 7; i++) xr[i] = xs[lane + 32 * i];
            float sum = 0.f;
#pragma unroll
            for (int i = 0; i < 7; i++) sum += bflo(xr[i]) + bfhi(xr[i]);
#pragma unroll
            for (int o = 16; o; o >>= 1) sum += __shfl_xor_sync(0xffffffffu, sum, o);
            const float mean = sum * (1.f / D_MODEL);
            float var = 0.f;
#pragma unroll
            for (int i = 0; i < 7; i++) { float a = bflo(xr[i]) - mean, b = bfhi(xr[i]) - mean; var += a * a + b * b; }
#pragma unroll
            for (int o = 16; o; o >>= 1) var += __shfl_xor_sync(0xffffffffu, var, o);
            const float mb = rbf(mean);
            const float den = rbf(__fsqrt_rn(rbf(rbf(var * (1.f / D_MODEL)) + 1e-5f)));
            if (w < 7) {
                float2 v;
                v.x = rbf(__fdiv_rn(rbf(bflo(xm) - mb), den));
                v.y = rbf(__fdiv_rn(rbf(bfhi(xm) - mb), den));
                *reinterpret_cast<float2*>(&xn_s[2 * t]) = v;
            }
        }
        bar_sync<1, NTHREADS>();
        cluster_arrive();
        const uint32_t tag = (ep_s + 1) & 3u;

        if (strm) {
            if (w == 0) stg_pub2(&p.s->qbox[cl][r * 64 + 2 * lane], tag ^ 2u, tag ^ 2u);
            {
                float a[8];
#pragma unroll
                for (int i = 0; i < 8; i++) a[i] = 0.f;
#pragma unroll 1
                for (int b = 0; b < 4; b++) {
                    mbar_wait(bar0 + (B_FULL + b) * 8, 0);
                    const uint32_t base = sm0 + b * TILE + t * 16;
                    const float* xs = &xn_s[b * 128 + (t >> 3)];
                    fma8(a, lds128(base), xs[0]);
                    fma8(a, lds128(base + 4096), xs[32]);
                    if (b < 3) {
                        fma8(a, lds128(base + 8192), xs[64]);
                        fma8(a, lds128(base + 12288), xs[96]);
                    }
                    __syncwarp();
                    if (lane == 0) mbar_arrive(bar0 + (B_EMPTY + b) * 8, 1);
                }
                halve<8, 16>(a, lane); halve<4, 8>(a, lane);
                *reinterpret_cast<float2*>(&red_s[w][(lane & 7) * 8 + (lane >> 3) * 2]) = make_float2(a[0], a[1]);
                bar_sync<3, 256>();
                if (w == 0) {
                    float q0 = 0.f, q1 = 0.f;
#pragma unroll
                    for (int i = 0; i < 8; i++) { const float2 v = *reinterpret_cast<const float2*>(&red_s[i][2 * lane]); q0 += v.x; q1 += v.y; }
                    stg_pub2(&p.s->qbox[cl][r * 64 + 2 * lane], __float_as_uint(rbf(q0)) | tag, __float_as_uint(rbf(q1)) | tag);
                }
            }
            mbar_wait(bar0 + B_Q * 8, 0);
            const uint32_t qa0 = s2u(&q_s[0][0]) + (g & 1) * 512 + tq4 * 16 + (((g >> 1) ^ g) & 1) * 64, qa1 = qa0 ^ 64;
            const uint32_t ka0 = sm0 + (w & 1) * 8192 + g * 512 + tq4 * 16 + (g & 1) * 64;
            const uint32_t sa = s2u(&sc_s[(w & 1) * 16 + g]);
#pragma unroll 1
            for (int i4 = 0; i4 < 4; i4++) {
                const int tile = (w >> 1) + 4 * i4, it = IT_K + tile;
                const int slot = it >= NS ? it - NS : it;
                uint4 qf[8];
#pragma unroll
                for (int i = 0; i < 8; i++) qf[i] = lds128((i & 1 ? qa1 : qa0) + (tile >> 1) * 1024 + (i >> 1) * 128);
                mbar_wait(bar0 + (B_FULL + it) * 8, 0);
                float ca[4] = {0.f, 0.f, 0.f, 0.f}, cb[4] = {0.f, 0.f, 0.f, 0.f};
                const uint32_t base0 = ka0 + slot * TILE, base1 = base0 ^ 64;
#pragma unroll
                for (int i = 0; i < 8; i++) {
                    const uint32_t a = (i & 1 ? base1 : base0) + (i >> 1) * 128;
                    const uint4 lo = lds128(a), hi = lds128(a + 4096);
                    mma16816(ca, lo.x, hi.x, lo.y, hi.y, qf[i].x, qf[i].y);
                    mma16816(cb, lo.z, hi.z, lo.w, hi.w, qf[i].z, qf[i].w);
                }
                if (lane == 0) mbar_arrive(bar0 + (B_EMPTY + slot) * 8, 4);
                if (tq4 == (g & 1)) {
                    const uint32_t s0 = pack_bf(ca[0] + cb[0], ca[1] + cb[1]), s1 = pack_bf(ca[2] + cb[2], ca[3] + cb[3]);
                    sts64f(sa + tile * 256, bflo(s0) * 0.0625f, bfhi(s0) * 0.0625f);
                    sts64f(sa + tile * 256 + 64, bflo(s1) * 0.0625f, bfhi(s1) * 0.0625f);
                }
            }
            bar_sync<3, 256>();
            {
                float4 s = *reinterpret_cast<const float4*>(&sc_s[2 * t]);
                float m0 = fmaxf(s.x, s.z), m1 = fmaxf(s.y, s.w);
#pragma unroll
                for (int o = 16; o; o >>= 1) { m0 = fmaxf(m0, __shfl_xor_sync(0xffffffffu, m0, o)); m1 = fmaxf(m1, __shfl_xor_sync(0xffffffffu, m1, o)); }
                s.x = exp2f((s.x - m0) * LOG2E); s.y = exp2f((s.y - m1) * LOG2E);
                s.z = exp2f((s.z - m0) * LOG2E); s.w = exp2f((s.w - m1) * LOG2E);
                const int pos = (t & ~15) + (t & 3) * 4 + ((t >> 2) & 3);
                p_s[0][pos] = pack_bf(s.x, s.z);
                p_s[1][pos] = pack_bf(s.y, s.w);
                float l0 = s.x + s.z, l1 = s.y + s.w;
#pragma unroll
                for (int o = 16; o; o >>= 1) { l0 += __shfl_xor_sync(0xffffffffu, l0, o); l1 += __shfl_xor_sync(0xffffffffu, l1, o); }
                cluster_wait();
                if (lane < 8) st_async2(mapa(s2u(&ml_s[w][r]), lane), __float_as_uint(lane < 4 ? m0 : m1), __float_as_uint(lane < 4 ? l0 : l1), mapa(bar0 + B_ML * 8, lane));
                bar_sync<3, 256>();
            }
            {
                const uint32_t lo = sm0 + (w >> 1) * 1024 + (lane & 7) * 128 + (lane >> 4) * 4096;
                const uint32_t sw = ((w & 1) * 4 + ((lane >> 3) & 1)) ^ (lane & 7);
                const uint32_t pa = s2u(&p_s[g & 1][tq4 * 4]);
                const int dst = (tq4 & 1) * 4 + (w >> 1);
                const uint32_t da = mapa(s2u(&in_s[0][r][(w & 1) * 32 + (tq4 >> 1) * 16 + g]), dst), db = mapa(bar0 + B_O * 8, dst);
                int slot = IT_V - NS;
#pragma unroll 1
                for (int h = 0; h < 8; h++) {
                    float acc[4][4];
#pragma unroll
                    for (int i = 0; i < 4; i++) { acc[i][0] = acc[i][1] = acc[i][2] = acc[i][3] = 0.f; }
#pragma unroll
                    for (int j = 0; j < 2; j++) {
                        const uint4 pf = lds128(pa + (2 * h + j) * 64);
                        const uint32_t base = lo + (slot + j) * TILE;
                        mbar_wait(bar0 + (B_FULL + IT_V + 2 * h + j) * 8, 0);
                        uint4 vf[4];
#pragma unroll
                        for (int i = 0; i < 4; i++) vf[i] = ldsm4t(base + (i >> 1) * 8192 + ((sw ^ (2 * (i & 1))) << 4));
                        mma16816(acc[0], vf[0].x, vf[0].y, vf[0].z, vf[0].w, pf.x, pf.y);
                        mma16816(acc[1], vf[1].x, vf[1].y, vf[1].z, vf[1].w, pf.x, pf.y);
                        mma16816(acc[2], vf[2].x, vf[2].y, vf[2].z, vf[2].w, pf.z, pf.w);
                        mma16816(acc[3], vf[3].x, vf[3].y, vf[3].z, vf[3].w, pf.z, pf.w);
                        if (lane == 0) mbar_arrive(bar0 + (B_EMPTY + slot + j) * 8, 1);
                    }
                    slot += 2;
                    if (slot == NS) slot = 0;
                    const bool hi = tq4 & 2, h1 = tq4 & 1;
                    const float x0 = hi ? acc[1][0] + acc[3][0] : acc[0][0] + acc[2][0], x1 = hi ? acc[1][1] + acc[3][1] : acc[0][1] + acc[2][1];
                    const float x2 = hi ? acc[1][2] + acc[3][2] : acc[0][2] + acc[2][2], x3 = hi ? acc[1][3] + acc[3][3] : acc[0][3] + acc[2][3];
                    st_async1(da + h * 2048, __float_as_uint(h1 ? x1 : x0), db + h * 8);
                    st_async1(da + h * 2048 + 32, __float_as_uint(h1 ? x3 : x2), db + h * 8);
                }
            }
        } else {
            const int k = cl - 8;
            if (w == 0) stg_pub1(&p.s->hbox[r][k * 32 + lane], tag ^ 2u);
            {
                float a[8];
#pragma unroll
                for (int i = 0; i < 8; i++) a[i] = 0.f;
                mbar_wait(bar0, 0);
#pragma unroll 1
                for (int i = 0; i < 7; i++) fma8(a, lds128(sm0 + (t + 256 * i) * 16), xn_s[(t >> 2) + 64 * i]);
                halve<8, 16>(a, lane); halve<4, 8>(a, lane); halve<2, 4>(a, lane);
                red_s[w][(lane & 3) * 8 + (lane >> 2)] = a[0];
                bar_sync<3, 256>();
                if (w == 0) {
                    float h = 0.f;
#pragma unroll
                    for (int i = 0; i < 8; i++) h += red_s[i][lane];
                    h = rbf(rbf(h) + b1_s[lane]);
                    const float u = 0.7978845608028654f * (h + 0.044715f * h * h * h);
                    stg_pub1(&p.s->hbox[r][k * 32 + lane], __float_as_uint(rbf(0.5f * h * (1.f + tanhf(u)))) | tag);
                }
                if (t < 56) {
                    uint4 v;
                    int it = 0;
                    do { __nanosleep(1000); v = ldg_poll(&p.s->hbox[r][t * 4]); } while (bad4(v, tag) && ++it < SPIN_LIMIT);
                    const int pi = 2 * t, pos = (pi & ~15) + (pi & 3) * 4 + ((pi >> 2) & 3);
                    h_s[pos] = __byte_perm(v.x, v.y, 0x7632);
                    h_s[pos + 4] = __byte_perm(v.z, v.w, 0x7632);
                }
                bar_sync<3, 256>();
            }
            cluster_wait();
            if (w < 6) gather_o(w);
            {
                float acc[2][4] = {{0.f, 0.f, 0.f, 0.f}, {0.f, 0.f, 0.f, 0.f}};
                const uint32_t base = sm0 + SM_W2 + ((lane & 7) + 16 * ((lane >> 3) & 1) + 8 * (lane >> 4)) * 128 + ((w ^ (lane & 7)) << 4);
                const uint32_t va = s2u(&h_s[tq4 * 4 + (g & 1) * 2]);
                const uint32_t da = mapa(s2u(&in_s[0][0][(32 + r) * 8 + g]), w), db = mapa(bar0 + B_F * 8, w);
                uint4 u0, u1;
                float2 b0, b1;
#pragma unroll
                for (int i = 0; i < 15; i++) {
                    uint4 n0, n1;
                    float2 c0, c1;
                    if (i == 13) {
                        mma16816(acc[0], u0.x, u0.y, u0.z, u0.w, __float_as_uint(b0.x), __float_as_uint(b0.y));
                        mma16816(acc[1], u1.x, u1.y, u1.z, u1.w, __float_as_uint(b1.x), __float_as_uint(b1.y));
                    }
                    if (i < 14) {
                        if (i == 7 || i == 13) mbar_wait(bar0 + (i == 7 ? B_O05 : B_O6) * 8, 0);
                        const int j = i < 7 ? i : 2 * i - 7;
                        c0 = lds64f(va + j * 64);
                        if (i >= 7) c1 = lds64f(va + j * 64 + 64);
                        mbar_wait(bar0 + (1 + i) * 8, 0);
                        n0 = ldsm4t(base + (i < 7 ? j : j + 1) * 4096);
                        if (i >= 7) n1 = ldsm4t(base + (j + 2) * 4096);
                    }
                    if (i > 0 && i != 13) {
                        mma16816(acc[i > 7 ? 0 : i & 1], u0.x, u0.y, u0.z, u0.w, __float_as_uint(b0.x), __float_as_uint(b0.y));
                        if (i > 7) mma16816(acc[1], u1.x, u1.y, u1.z, u1.w, __float_as_uint(b1.x), __float_as_uint(b1.y));
                    }
                    u0 = n0; u1 = n1; b0 = c0; b1 = c1;
                }
                if (tq4 == 0) st_async1(da, __float_as_uint((acc[0][0] + acc[0][3]) + (acc[1][0] + acc[1][3])), db);
            }
        }
    } else {
        const int fw = warp - 9, t = threadIdx.x - 288;
        if (fw == 0) {
            if (elect()) {
#pragma unroll
                for (int i = IT_K + 1; i < NBAR; i++) mbar_init(bar0 + i * 8, (i >= B_EMPTY && i < B_Q) ? 8 : 1);
                mbar_fence_init();
            }
            __syncwarp();
            bar_arrive<2, 64>();
            if (elect()) {
                mbar_expect(bar0 + B_Q * 8, 8192);
                mbar_expect(bar0 + B_ML * 8, strm ? 512 : 1024);
                mbar_expect(bar0 + B_F * 8, 256);
#pragma unroll
                for (int i = 0; i < 8; i++) mbar_expect(bar0 + (B_O + i) * 8, 2048);
            }
            __syncwarp();
        } else if (fw == 1) {
            uint32_t e;
            asm volatile("ld.relaxed.gpu.global.u32 %0, [%1];" : "=r"(e) : "l"(&p.s->epoch) : "memory");
            if (lane == 0) ep_s = e;
        } else if (!strm) {
            if (fw == 2) {
                b1_s[lane] = __bfloat162float(p.b1[(c - 64) * 32 + lane]);
            } else if (fw == 3) {
                const int col = (c - 64) * 8 + (lane & 7);
                if (lane < 8) b1_s[32 + lane] = __bfloat162float(p.x[col]) + __bfloat162float(p.b2[col]);
            }
        }
        bar_sync<1, NTHREADS>();
        cluster_arrive();
        const uint32_t tag = (ep_s + 1) & 3u;
        if (fw == 4) {
            if (!strm) {
                const uint32_t g0 = g0_s;
                while (gtime() - g0 < p.tt) __nanosleep(200);
                uint32_t v;
                int it = 0;
                while (true) {
                    asm volatile("ld.relaxed.gpu.global.u32 %0, [%1];" : "=r"(v) : "l"(&p.s->tbox[r][lane & 7][0]) : "memory");
                    if (!__any_sync(0xffffffffu, (v ^ tag) & 3u) || ++it >= SPIN_LIMIT) break;
                    __nanosleep(100);
                }
                int sum = (int)(v - g0 - p.tn);
#pragma unroll
                for (int o = 1; o < 8; o <<= 1) sum += __shfl_xor_sync(0xffffffffu, sum, o);
                if (lane == 0) {
                    *reinterpret_cast<volatile uint32_t*>(&g0_s) = g0 + (min(max(sum, -8 * 800), 8 * 4000) >> 3);
                    mbar_arrive(bar0 + B_TIME * 8, 1);
                }
                __syncwarp();
                gather_o(6);
            }
        } else if (strm) {
            {
                uint4 v;
                int it = 0;
                mbar_wait(bar0 + (B_EMPTY + 3) * 8, 0);
                while (true) {
                    __nanosleep(it ? 150 : 500);
                    v = ldg_poll(&p.s->qbox[r][t * 4]);
                    if (!bad4(v, tag) || ++it >= SPIN_LIMIT) break;
                }
                __syncwarp();
                cluster_wait();
                const uint32_t lo = __byte_perm(v.x, v.y, 0x7632), hi = __byte_perm(v.z, v.w, 0x7632);
#pragma unroll
                for (int d = 0; d < 8; d++) st_async2(mapa(s2u(&q_s[r][(t * 2) ^ ((t >> 6) * 16)]), d), lo, hi, mapa(bar0 + B_Q * 8, d));
            }
            if (fw == 0) {
                uint32_t* dst = &p.s->obox[0][r][cl][(lane >> 3) * 16 + (lane & 3) * 4 + ((lane >> 2) & 1) * 2];
#pragma unroll
                for (int h = 0; h < 8; h++) stg_pub2(dst + h * 4096, tag ^ 2u, tag ^ 2u);
                if ((lane & 7) == 0) { stg_pub2(&p.s->sbox[r][cl][2 * (lane >> 3)], tag ^ 2u, tag ^ 2u); stg_pub2(&p.s->sbox[r][cl][2 * (lane >> 3) + 8], tag ^ 2u, tag ^ 2u); }
                if (lane < 8) stg_pub1(&p.s->tbox[r][cl][lane], tag ^ 2u);
                mbar_wait(bar0 + B_ML * 8, 0);
                float e[2];
#pragma unroll
                for (int i = 0; i < 2; i++) {
                    const float2 v = ml_s[(lane >> 3) + 4 * i][lane & 7];
                    float M = v.x;
#pragma unroll
                    for (int o = 1; o < 8; o <<= 1) M = fmaxf(M, __shfl_xor_sync(0xffffffffu, M, o));
                    e[i] = exp2f((v.x - M) * LOG2E);
                    float L = v.y * e[i];
#pragma unroll
                    for (int o = 1; o < 8; o <<= 1) L += __shfl_xor_sync(0xffffffffu, L, o);
                    if ((lane & 7) == 0) stg_pub2(&p.s->sbox[r][cl][2 * ((lane >> 3) + 4 * i)], tagf(M, tag), tagf(L, tag));
                }
#pragma unroll 1
                for (int h = 0; h < 8; h++) {
                    float ws[8];
#pragma unroll
                    for (int s = 0; s < 8; s++) ws[s] = __shfl_sync(0xffffffffu, h < 4 ? e[0] : e[1], (h & 3) * 8 + s);
                    mbar_wait(bar0 + (B_O + h) * 8, 0);
                    float2 ov[8];
#pragma unroll
                    for (int s = 0; s < 8; s++) ov[s] = lds64f(s2u(&in_s[h][s][2 * lane]));
                    const float o0 = (fmaf(ov[0].x, ws[0], ov[1].x * ws[1]) + fmaf(ov[2].x, ws[2], ov[3].x * ws[3])) + (fmaf(ov[4].x, ws[4], ov[5].x * ws[5]) + fmaf(ov[6].x, ws[6], ov[7].x * ws[7]));
                    const float o1 = (fmaf(ov[0].y, ws[0], ov[1].y * ws[1]) + fmaf(ov[2].y, ws[2], ov[3].y * ws[3])) + (fmaf(ov[4].y, ws[4], ov[5].y * ws[5]) + fmaf(ov[6].y, ws[6], ov[7].y * ws[7]));
                    stg_pub2(dst + h * 4096, tagf(o0, tag), tagf(o1, tag));
                    if (h == 1 && lane < 8) stg_pub1(&p.s->tbox[r][cl][lane], (gtime() & ~3u) | tag);
                }
            }
        } else {
            const int g = lane >> 2, tq4 = lane & 3;
            { const uint32_t g0 = g0_s; while (gtime() - g0 < p.ts) __nanosleep(300); }
            float wgt[2];
            {
                uint4 v;
                int it = 0;
                while (true) {
                    v = ldg_poll(&p.s->sbox[r][g][4 * tq4]);
                    if (!__any_sync(0xffffffffu, bad4(v, tag)) || ++it >= SPIN_LIMIT) break;
                    __nanosleep(300);
                }
#pragma unroll
                for (int i = 0; i < 2; i++) {
                    const float m = __uint_as_float((i ? v.z : v.x) & ~3u);
                    float M = m;
#pragma unroll
                    for (int o = 4; o < 32; o <<= 1) M = fmaxf(M, __shfl_xor_sync(0xffffffffu, M, o));
                    const float e = exp2f((m - M) * LOG2E);
                    float L = __uint_as_float((i ? v.w : v.y) & ~3u) * e;
#pragma unroll
                    for (int o = 4; o < 32; o <<= 1) L += __shfl_xor_sync(0xffffffffu, L, o);
                    wgt[i] = __fdividef(e, L);
                }
                if (fw == 0) {
                    ml_s[2 * tq4][g].x = wgt[0]; ml_s[2 * tq4 + 1][g].x = wgt[1];
                    __syncwarp();
                    if (lane == 0) mbar_arrive(bar0 + B_WGT * 8, 1);
                }
            }
            const uint32_t fa = s2u(&in_s[0][0][(r * 4 + fw) * 8 + g]);
            const uint32_t da0 = mapa(fa, 2 * tq4), db0 = mapa(bar0 + B_F7 * 8, 2 * tq4), da1 = mapa(fa, 2 * tq4 + 1), db1 = mapa(bar0 + B_F7 * 8, 2 * tq4 + 1);
            const float wg7 = __shfl_sync(0xffffffffu, wgt[1], (lane & 28) + 3);
            cluster_wait();
            mbar_wait(bar0 + 15 * 8, 0);
            uint4 wf[4];
#pragma unroll
            for (int j = 0; j < 4; j++)
                wf[j] = ldsm4t(sm0 + SM_WO + 7 * 8192 + fw * 2048 + ((lane & 7) + 8 * (lane >> 4)) * 128 + (((2 * j + ((lane >> 3) & 1)) ^ (lane & 7)) << 4));
            const uint32_t* src = &p.s->obox[7][r][g][fw * 16 + tq4 * 4];
            uint4 ov;
            {
                while (gtime() - *reinterpret_cast<volatile uint32_t*>(&g0_s) < p.to7) __nanosleep(64);
                int it = 0;
                do { ov = ldg_poll(src); } while (__any_sync(0xffffffffu, bad4(ov, tag)) && ++it < SPIN_LIMIT);
            }
            const uint32_t b0 = pack_bf(__uint_as_float(ov.x) * wg7, __uint_as_float(ov.y) * wg7), b1 = pack_bf(__uint_as_float(ov.z) * wg7, __uint_as_float(ov.w) * wg7);
            float a[8];
#pragma unroll
            for (int j = 0; j < 4; j++) {
                float acc[4] = {0.f, 0.f, 0.f, 0.f};
                mma16816(acc, wf[j].x, wf[j].y, wf[j].z, wf[j].w, b0, b1);
                a[2 * j] = acc[0] + acc[1]; a[2 * j + 1] = acc[2] + acc[3];
            }
            halve<8, 2>(a, lane); halve<4, 1>(a, lane);
            st_async1(da0, __float_as_uint(a[0]), db0);
            st_async1(da1, __float_as_uint(a[1]), db1);
            if (fw == 0) {
                const float base = b1_s[32 + (lane & 7)];
                __nv_bfloat16* dst = p.out + (c - 64) * 8 + (lane & 7);
                const volatile float* in = &in_s[0][0][0];
                float s[8];
                mbar_wait(bar0 + B_F7 * 8, 0);
#pragma unroll
                for (int i = 0; i < 8; i++) s[i] = in[i * 32 + lane];
                float v = ((s[0] + s[1]) + (s[2] + s[3])) + ((s[4] + s[5]) + (s[6] + s[7]));
                v += __shfl_xor_sync(0xffffffffu, v, 8);
                v += __shfl_xor_sync(0xffffffffu, v, 16);
                v += base;
                mbar_wait(bar0 + B_F * 8, 0);
#pragma unroll
                for (int i = 0; i < 8; i++) s[i] = in[256 + i * 8 + (lane & 7)];
                v += ((s[0] + s[1]) + (s[2] + s[3])) + ((s[4] + s[5]) + (s[6] + s[7]));
                if (lane < 8) *dst = __float2bfloat16_rn(v);
                if (c == 64 && lane == 0) p.s->epoch = ep_s + 1;
            }
        }
    }
}

typedef CUresult (*EncodeFn)(CUtensorMap*, CUtensorMapDataType, cuuint32_t, void*, const cuuint64_t*, const cuuint64_t*,
                             const cuuint32_t*, const cuuint32_t*, CUtensorMapInterleave, CUtensorMapSwizzle,
                             CUtensorMapL2promotion, CUtensorMapFloatOOBfill);

void make_map(EncodeFn encode, CUtensorMap* m, void* base, uint64_t cols, uint64_t rows, uint32_t bc, uint32_t br, bool swz) {
    cuuint64_t gd[2] = {cols, rows}; cuuint64_t gs[1] = {cols * 2}; cuuint32_t bd[2] = {bc, br}; cuuint32_t es[2] = {1, 1};
    encode(m, CU_TENSOR_MAP_DATA_TYPE_BFLOAT16, 2, base, gd, gs, bd, es, CU_TENSOR_MAP_INTERLEAVE_NONE,
           swz ? CU_TENSOR_MAP_SWIZZLE_128B : CU_TENSOR_MAP_SWIZZLE_NONE, CU_TENSOR_MAP_L2_PROMOTION_L2_128B, CU_TENSOR_MAP_FLOAT_OOB_FILL_NONE);
}

}

static const uint32_t g_cfg[12] = {5100, 1500, 500, 9300, 11650, 1400, 2450, 13030, 13430, 9750, 9270, 650};

extern "C" void kernel_launch(void* const* d_in, const int* in_sizes, int n_in, void* d_out, int out_size) {
    (void)in_sizes; (void)n_in; (void)out_size;
    static EncodeFn encode = nullptr;
    static Scratch* scratch = nullptr;
    static double f = 1.0;
    if (!encode) {
        void* fn = nullptr;
        cudaDriverEntryPointQueryResult st;
        cudaGetDriverEntryPoint("cuTensorMapEncodeTiled", &fn, cudaEnableDefault, &st);
        encode = (EncodeFn)fn;
        cudaGetSymbolAddress((void**)&scratch, g_scratch);
        int dev = 0, khz = 0, bits = 0;
        cudaGetDevice(&dev);
        cudaDeviceGetAttribute(&khz, cudaDevAttrMemoryClockRate, dev);
        cudaDeviceGetAttribute(&bits, cudaDevAttrGlobalMemoryBusWidth, dev);
        if (khz > 0 && bits > 0) f = (2619000.0 * 5120.0) / ((double)khz * bits);
        cudaFuncSetAttribute(fused_decode_kernel, cudaFuncAttributeMaxDynamicSharedMemorySize, SM_DYN);
    }
    CUtensorMap tq, t1, t2, tv, to;
    make_map(encode, &tq, d_in[3], 4096, D_MODEL, 64, 128, false);
    make_map(encode, &t1, d_in[6], FFN, D_MODEL, 32, 224, false);
    make_map(encode, &t2, d_in[8], D_MODEL, FFN, 64, 32, true);
    make_map(encode, &to, d_in[4], D_MODEL, 4096, 64, 64, true);
    {
        cuuint64_t gd[4] = {64, 8, 4, (cuuint64_t)SK}; cuuint64_t gs[3] = {512, 128, 4096}; cuuint32_t bd[4] = {64, 8, 4, 4}; cuuint32_t es[4] = {1, 1, 1, 1};
        encode(&tv, CU_TENSOR_MAP_DATA_TYPE_BFLOAT16, 4, d_in[2], gd, gs, bd, es, CU_TENSOR_MAP_INTERLEAVE_NONE,
               CU_TENSOR_MAP_SWIZZLE_128B, CU_TENSOR_MAP_L2_PROMOTION_NONE, CU_TENSOR_MAP_FLOAT_OOB_FILL_NONE);
    }
    Params p;
    p.x = (const __nv_bfloat16*)d_in[0];
    p.k = (const char*)d_in[1];
    p.b1 = (const __nv_bfloat16*)d_in[7];
    p.b2 = (const __nv_bfloat16*)d_in[9];
    p.out = (__nv_bfloat16*)d_out;
    p.s = scratch;
    auto sc = [&](int i, double fixed) { return (uint32_t)(fixed + (g_cfg[i] - fixed) * f + 0.5); };
    p.pace = sc(0, 0); p.t0 = sc(1, 0); p.tw1 = sc(2, 0); p.ts = sc(3, 2000); p.tw2 = sc(4, 0); p.pace_w2 = sc(5, 0); p.pace_wo = sc(6, 0);
    p.to6 = sc(7, 1500); p.to7 = sc(8, 1300); p.tt = sc(9, 1400); p.tn = sc(10, 1000); p.th = sc(11, 0);
    fused_decode_kernel<<<NCTA, NTHREADS, SM_DYN, cudaStreamPerThread>>>(p, tq, t1, t2, tv, to);
}
```

```cpp
#include <cuda_runtime.h>
#include <cuda_bf16.h>
#include <cuda.h>
#include <stdint.h>

namespace {

constexpr int D_MODEL = 448;
constexpr int FFN = 1792;
constexpr int SK = 65536;
constexpr int WKEYS = 4096;
constexpr int NCTA = 120;
constexpr int TILE = 16384;
constexpr int NS = 12;
constexpr int NTHREADS = 32 * (1 + 8 + 5);
constexpr int SPIN_LIMIT = 1 << 20;
constexpr float LOG2E = 1.4426950408889634f;

constexpr int IT_K = 4, IT_V = 20, NIT = 36;
constexpr int B_FULL = 0, B_EMPTY = NIT, B_Q = NIT + NS, B_ML = B_Q + 1, B_F = B_Q + 2, B_O = B_Q + 3, NBAR = B_O + 8;
constexpr int B_WGT = 16, B_O05 = B_EMPTY, B_O6 = B_EMPTY + 1, B_F7 = B_ML;
constexpr int SM_W2 = 2 * TILE, SM_WO = 4 * TILE;
constexpr int SM_DYN = NS * TILE;

struct Scratch {
    uint32_t qbox[8][512];
    uint32_t hbox[8][256];
    uint32_t sbox[8][8][16];
    uint32_t obox[8][8][8][64];
    uint32_t epoch;
    uint32_t pad[31];
};
__device__ __align__(128) Scratch g_scratch;

struct Params {
    const __nv_bfloat16* x;
    const char* k;
    const __nv_bfloat16* b1;
    const __nv_bfloat16* b2;
    __nv_bfloat16* out;
    Scratch* s;
    uint32_t pace;
    uint32_t t0;
    uint32_t tw1;
    uint32_t ts;
    uint32_t tw2;
    uint32_t pace_w2;
    uint32_t pace_wo;
    uint32_t th;
    uint32_t to6, to7;
};

__device__ __forceinline__ uint32_t s2u(const void* p) { return (uint32_t)__cvta_generic_to_shared(p); }
__device__ __forceinline__ void mbar_init(uint32_t b, uint32_t c) { asm volatile("mbarrier.init.shared::cta.b64 [%0], %1;" :: "r"(b), "r"(c) : "memory"); }
__device__ __forceinline__ void mbar_fence_init() { asm volatile("fence.mbarrier_init.release.cluster;" ::: "memory"); }
__device__ __forceinline__ void mbar_expect(uint32_t b, uint32_t bytes) { asm volatile("mbarrier.arrive.expect_tx.shared::cta.b64 _, [%0], %1;" :: "r"(b), "r"(bytes) : "memory"); }
__device__ __forceinline__ void mbar_arrive(uint32_t b, uint32_t n) { asm volatile("mbarrier.arrive.shared::cta.b64 _, [%0], %1;" :: "r"(b), "r"(n) : "memory"); }
__device__ __forceinline__ void mbar_wait(uint32_t b, uint32_t ph) {
    asm volatile("{\n.reg .pred p;\nW: mbarrier.try_wait.parity.shared::cta.b64 p, [%0], %1;\n@p bra D;\nbra W;\nD:\n}" :: "r"(b), "r"(ph) : "memory");
}
__device__ __forceinline__ void bulk(uint32_t dst, const void* src, uint32_t bytes, uint32_t bar, uint64_t pol) {
    asm volatile("cp.async.bulk.shared::cluster.global.mbarrier::complete_tx::bytes.L2::cache_hint [%0], [%1], %2, [%3], %4;" :: "r"(dst), "l"(src), "r"(bytes), "r"(bar), "l"(pol) : "memory");
}
__device__ __forceinline__ void tma2d(uint32_t dst, const void* tm, int x, int y, uint32_t bar) {
    asm volatile("cp.async.bulk.tensor.2d.shared::cluster.global.mbarrier::complete_tx::bytes [%0], [%1, {%3, %4}], [%2];" :: "r"(dst), "l"(tm), "r"(bar), "r"(x), "r"(y) : "memory");
}
__device__ __forceinline__ void tma4d(uint32_t dst, const void* tm, int y, uint32_t bar, uint64_t pol) {
    asm volatile("cp.async.bulk.tensor.4d.shared::cluster.global.mbarrier::complete_tx::bytes.L2::cache_hint [%0], [%1, {0, 0, 0, %3}], [%2], %4;" :: "r"(dst), "l"(tm), "r"(bar), "r"(y), "l"(pol) : "memory");
}
__device__ __forceinline__ uint4 ldsm4t(uint32_t a) { uint4 v; asm volatile("ldmatrix.sync.aligned.m8n8.x4.trans.shared.b16 {%0,%1,%2,%3}, [%4];" : "=r"(v.x), "=r"(v.y), "=r"(v.z), "=r"(v.w) : "r"(a)); return v; }
__device__ __forceinline__ uint32_t mapa(uint32_t a, uint32_t r) { uint32_t d; asm("mapa.shared::cluster.u32 %0, %1, %2;" : "=r"(d) : "r"(a), "r"(r)); return d; }
__device__ __forceinline__ void st_async1(uint32_t a, uint32_t x, uint32_t bar) {
    asm volatile("st.async.weak.shared::cluster.mbarrier::complete_tx::bytes.b32 [%0], %1, [%2];" :: "r"(a), "r"(x), "r"(bar) : "memory");
}
__device__ __forceinline__ void st_async2(uint32_t a, uint32_t x, uint32_t y, uint32_t bar) {
    asm volatile("st.async.weak.shared::cluster.mbarrier::complete_tx::bytes.v2.b32 [%0], {%1, %2}, [%3];" :: "r"(a), "r"(x), "r"(y), "r"(bar) : "memory");
}
__device__ __forceinline__ void cluster_arrive() { asm volatile("barrier.cluster.arrive.relaxed.aligned;" ::: "memory"); }
__device__ __forceinline__ void cluster_wait() { asm volatile("barrier.cluster.wait.aligned;" ::: "memory"); }
__device__ __forceinline__ bool elect() { uint32_t r; asm volatile("{\n.reg .pred p;\nelect.sync _|p, 0xffffffff;\nselp.u32 %0,1,0,p;\n}" : "=r"(r)); return r; }
__device__ __forceinline__ uint32_t gtime() { uint32_t t; asm volatile("mov.u32 %0, %globaltimer_lo;" : "=r"(t) :: "memory"); return t; }
template <int ID, int N> __device__ __forceinline__ void bar_sync() { asm volatile("bar.sync %0, %1;" :: "n"(ID), "n"(N) : "memory"); }
template <int ID, int N> __device__ __forceinline__ void bar_arrive() { asm volatile("bar.arrive %0, %1;" :: "n"(ID), "n"(N) : "memory"); }
__device__ __forceinline__ uint4 lds128(uint32_t a) { uint4 v; asm volatile("ld.shared.v4.u32 {%0,%1,%2,%3}, [%4];" : "=r"(v.x), "=r"(v.y), "=r"(v.z), "=r"(v.w) : "r"(a)); return v; }
__device__ __forceinline__ float2 lds64f(uint32_t a) { float2 v; asm volatile("ld.shared.v2.f32 {%0,%1}, [%2];" : "=f"(v.x), "=f"(v.y) : "r"(a)); return v; }
__device__ __forceinline__ void sts64f(uint32_t a, float x, float y) { asm volatile("st.shared.v2.f32 [%0], {%1,%2};" :: "r"(a), "f"(x), "f"(y) : "memory"); }
__device__ __forceinline__ uint4 ldg_poll(const void* p) { uint4 v; asm volatile("ld.relaxed.gpu.global.v4.u32 {%0,%1,%2,%3}, [%4];" : "=r"(v.x), "=r"(v.y), "=r"(v.z), "=r"(v.w) : "l"(p) : "memory"); return v; }
__device__ __forceinline__ void stg_pub2(void* p, uint32_t a, uint32_t b) { asm volatile("st.relaxed.gpu.global.v2.u32 [%0], {%1,%2};" :: "l"(p), "r"(a), "r"(b) : "memory"); }
__device__ __forceinline__ void stg_pub1(void* p, uint32_t a) { asm volatile("st.relaxed.gpu.global.u32 [%0], %1;" :: "l"(p), "r"(a) : "memory"); }
__device__ __forceinline__ uint32_t bad4(uint4 v, uint32_t tag) { return ((v.x ^ tag) | (v.y ^ tag) | (v.z ^ tag) | (v.w ^ tag)) & 3u; }
__device__ __forceinline__ uint32_t tagf(float f, uint32_t tag) { return (__float_as_uint(f) & ~3u) | tag; }
__device__ __forceinline__ float bflo(uint32_t u) { return __uint_as_float(u << 16); }
__device__ __forceinline__ float bfhi(uint32_t u) { return __uint_as_float(u & 0xffff0000u); }
__device__ __forceinline__ float rbf(float f) { return __bfloat162float(__float2bfloat16_rn(f)); }
__device__ __forceinline__ uint32_t pack_bf(float lo, float hi) { const __nv_bfloat162 r = __floats2bfloat162_rn(lo, hi); return *reinterpret_cast<const uint32_t*>(&r); }
__device__ __forceinline__ void fma8(float* a, uint4 w, float s) {
    a[0] = fmaf(bflo(w.x), s, a[0]); a[1] = fmaf(bfhi(w.x), s, a[1]);
    a[2] = fmaf(bflo(w.y), s, a[2]); a[3] = fmaf(bfhi(w.y), s, a[3]);
    a[4] = fmaf(bflo(w.z), s, a[4]); a[5] = fmaf(bfhi(w.z), s, a[5]);
    a[6] = fmaf(bflo(w.w), s, a[6]); a[7] = fmaf(bfhi(w.w), s, a[7]);
}
template <int N, int M> __device__ __forceinline__ void halve(float* a, int lane) {
    const bool up = lane & M;
#pragma unroll
    for (int i = 0; i < N / 2; i++) {
        float keep = up ? a[i + N / 2] : a[i];
        float send = up ? a[i] : a[i + N / 2];
        a[i] = keep + __shfl_xor_sync(0xffffffffu, send, M);
    }
}
__device__ __forceinline__ void mma16816(float* c, uint32_t a0, uint32_t a1, uint32_t a2, uint32_t a3, uint32_t b0, uint32_t b1) {
    asm volatile("mma.sync.aligned.m16n8k16.row.col.f32.bf16.bf16.f32 {%0,%1,%2,%3}, {%4,%5,%6,%7}, {%8,%9}, {%0,%1,%2,%3};"
                 : "+f"(c[0]), "+f"(c[1]), "+f"(c[2]), "+f"(c[3]) : "r"(a0), "r"(a1), "r"(a2), "r"(a3), "r"(b0), "r"(b1));
}

__global__ void __cluster_dims__(8, 1, 1) __launch_bounds__(NTHREADS, 1)
fused_decode_kernel(const __grid_constant__ Params p, const __grid_constant__ CUtensorMap tq,
                    const __grid_constant__ CUtensorMap t1, const __grid_constant__ CUtensorMap t2,
                    const __grid_constant__ CUtensorMap tv, const __grid_constant__ CUtensorMap to) {
    extern __shared__ __align__(1024) char sm[];
    __shared__ __align__(8) uint64_t bars[NBAR];
    __shared__ __align__(16) float xn_s[D_MODEL];
    __shared__ __align__(16) float red_s[8][64];
    __shared__ __align__(128) uint32_t q_s[8][256];
    __shared__ __align__(16) float2 sc_s[512];
    __shared__ __align__(16) float2 ml_s[8][8];
    __shared__ __align__(16) float in_s[8][8][64];
    __shared__ float b1_s[40];
    __shared__ uint32_t ep_s, g0_s;

    uint32_t (*p_s)[256] = reinterpret_cast<uint32_t (*)[256]>(red_s);
    uint32_t* h_s = reinterpret_cast<uint32_t*>(sc_s);
    const int c = blockIdx.x;
    const uint32_t bar0 = s2u(bars), sm0 = s2u(sm);
    const int cl = c >> 3, r = c & 7;
    const bool strm = cl < 8;
    const int warp = __shfl_sync(0xffffffffu, threadIdx.x >> 5, 0);
    int lane;
    asm volatile("mov.u32 %0, %laneid;" : "=r"(lane));

    auto gather_o = [&](int h) {
        const int g = lane >> 2, tq4 = lane & 3;
        mbar_wait(bar0 + B_WGT * 8, 0);
        const uint32_t tag = (ep_s + 1) & 3u;
        const float wg = ml_s[h][g].x;
        const uint32_t due = p.to6 - (6 - h) * p.th, g0 = g0_s;
        while (gtime() - g0 < due) __nanosleep(64);
        const uint32_t* src = &p.s->obox[h][r][g][tq4 * 4];
        uint4 ov[4];
        int it = 0;
        while (true) {
#pragma unroll
            for (int i = 0; i < 4; i++) ov[i] = ldg_poll(src + i * 16);
            const uint32_t bad = (bad4(ov[3], tag) | bad4(ov[2], tag)) | (bad4(ov[1], tag) | bad4(ov[0], tag));
            if (!__any_sync(0xffffffffu, bad) || ++it >= SPIN_LIMIT) break;
            __nanosleep(100);
        }
        float a[16];
#pragma unroll
        for (int i = 0; i < 4; i++) {
            a[4 * i] = __uint_as_float(ov[i].x) * wg; a[4 * i + 1] = __uint_as_float(ov[i].y) * wg;
            a[4 * i + 2] = __uint_as_float(ov[i].z) * wg; a[4 * i + 3] = __uint_as_float(ov[i].w) * wg;
        }
        halve<16, 16>(a, lane); halve<8, 8>(a, lane); halve<4, 4>(a, lane);
        h_s[(7 + 2 * h + (g >> 2)) * 16 + tq4 * 4 + (g & 3)] = pack_bf(a[0], a[1]);
        __syncwarp();
        if (lane == 0) mbar_arrive(bar0 + (h == 6 ? B_O6 : B_O05) * 8, h == 6 ? 8 : h < 2 ? 2 : 1);
    };

    if (warp == 0) {
        uint32_t g0 = 0;
        uint64_t pol;
        asm volatile("createpolicy.fractional.L2::evict_first.b64 %0, 1.0;" : "=l"(pol));
        const int row0 = SK - WKEYS + c * 32;
        if (elect()) {
#pragma unroll
            for (int i = 0; i <= IT_K; i++) mbar_init(bar0 + i * 8, 1);
            mbar_fence_init();
            if (strm) {
                mbar_expect(bar0 + IT_K * 8, TILE);
                bulk(sm0 + IT_K * TILE, p.k + (size_t)row0 * 512, TILE, bar0 + IT_K * 8, pol);
#pragma unroll
                for (int i = 0; i < 4; i++) { mbar_expect(bar0 + i * 8, TILE); tma2d(sm0 + i * TILE, &tq, c * 64, i * 128, bar0 + i * 8); }
            }
            g0 = gtime();
            g0_s = g0;
        }
        __syncwarp();
        bar_arrive<1, NTHREADS>();
        bar_sync<2, 64>();
        cluster_arrive();
        if (elect()) {
            if (strm) {
                asm volatile("prefetch.tensormap [%0];" :: "l"(&tv) : "memory");
                uint32_t target = p.t0 * 16;
                int slot = IT_K + 1, ph = 1;
#pragma unroll 1
                for (int it = IT_K + 1; it < NIT; it++) {
                    mbar_wait(bar0 + (B_EMPTY + slot) * 8, ph);
                    while ((gtime() - g0) * 16 < target) { }
                    target += p.pace;
                    const uint32_t b = bar0 + (B_FULL + it) * 8, dst = sm0 + slot * TILE;
                    const int tt = (it - IT_K) & 15, row = row0 + (tt >> 1) * SK + (tt & 1) * 2048;
                    mbar_expect(b, TILE);
                    if (it < IT_V) bulk(dst, p.k + (size_t)row * 512, TILE, b, pol);
                    else tma4d(dst, &tv, row >> 3, b, pol);
                    if (++slot == NS) { slot = 0; ph ^= 1; }
                }
            } else {
                const int k = cl - 8;
                while (gtime() - g0 < p.tw1) { }
                mbar_expect(bar0, 28672);
                tma2d(sm0, &t1, (c - 64) * 32, 0, bar0);
                tma2d(sm0 + 14336, &t1, (c - 64) * 32, 224, bar0);
                asm volatile("prefetch.tensormap [%0];" :: "l"(&t2) : "memory");
                asm volatile("prefetch.tensormap [%0];" :: "l"(&to) : "memory");
                while (gtime() - g0 + 400 < p.tw2) __nanosleep(100);
                uint32_t target = p.tw2 * 16;
                while ((gtime() - g0) * 16 < target) { }
                mbar_expect(bar0 + 15 * 8, 8192);
                tma2d(sm0 + SM_WO + 7 * 8192, &to, k * 64, 7 * 512 + r * 64, bar0 + 15 * 8);
                target += p.pace_wo;
#pragma unroll 1
                for (int i = 0; i < 14; i++) {
                    while ((gtime() - g0) * 16 < target) { }
                    const uint32_t b = bar0 + (1 + i) * 8;
                    if (i < 7) {
                        target += p.pace_w2;
                        mbar_expect(b, 4096);
                        tma2d(sm0 + SM_W2 + i * 4096, &t2, k * 64, i * 256 + r * 32, b);
                    } else {
                        target += p.pace_wo;
                        mbar_expect(b, 8192);
                        tma2d(sm0 + SM_WO + (i - 7) * 8192, &to, k * 64, (i - 7) * 512 + r * 64, b);
                    }
                }
            }
        }
    } else if (warp <= 8) {
        const int w = warp - 1, t = threadIdx.x - 32;
        const int g = lane >> 2, tq4 = lane & 3;
        {
            uint32_t* xs = reinterpret_cast<uint32_t*>(sc_s);
            const uint32_t xm = w < 7 ? __ldg(reinterpret_cast<const uint32_t*>(p.x) + t) : 0u;
            xs[t] = xm;
            bar_sync<3, 256>();
            uint32_t xr[7];
#pragma unroll
            for (int i = 0; i < 7; i++) xr[i] = xs[lane + 32 * i];
            float sum = 0.f;
#pragma unroll
            for (int i = 0; i < 7; i++) sum += bflo(xr[i]) + bfhi(xr[i]);
#pragma unroll
            for (int o = 16; o; o >>= 1) sum += __shfl_xor_sync(0xffffffffu, sum, o);
            const float mean = sum * (1.f / D_MODEL);
            float var = 0.f;
#pragma unroll
            for (int i = 0; i < 7; i++) { float a = bflo(xr[i]) - mean, b = bfhi(xr[i]) - mean; var += a * a + b * b; }
#pragma unroll
            for (int o = 16; o; o >>= 1) var += __shfl_xor_sync(0xffffffffu, var, o);
            const float mb = rbf(mean);
            const float den = rbf(__fsqrt_rn(rbf(rbf(var * (1.f / D_MODEL)) + 1e-5f)));
            if (w < 7) {
                float2 v;
                v.x = rbf(__fdiv_rn(rbf(bflo(xm) - mb), den));
                v.y = rbf(__fdiv_rn(rbf(bfhi(xm) - mb), den));
                *reinterpret_cast<float2*>(&xn_s[2 * t]) = v;
            }
        }
        bar_sync<1, NTHREADS>();
        cluster_arrive();
        const uint32_t tag = (ep_s + 1) & 3u;

        if (strm) {
            if (w == 0) stg_pub2(&p.s->qbox[cl][r * 64 + 2 * lane], tag ^ 2u, tag ^ 2u);
            {
                float a[8];
#pragma unroll
                for (int i = 0; i < 8; i++) a[i] = 0.f;
#pragma unroll 1
                for (int b = 0; b < 4; b++) {
                    mbar_wait(bar0 + (B_FULL + b) * 8, 0);
                    const uint32_t base = sm0 + b * TILE + t * 16;
                    const float* xs = &xn_s[b * 128 + (t >> 3)];
                    fma8(a, lds128(base), xs[0]);
                    fma8(a, lds128(base + 4096), xs[32]);
                    if (b < 3) {
                        fma8(a, lds128(base + 8192), xs[64]);
                        fma8(a, lds128(base + 12288), xs[96]);
                    }
                    __syncwarp();
                    if (lane == 0) mbar_arrive(bar0 + (B_EMPTY + b) * 8, 1);
                }
                halve<8, 16>(a, lane); halve<4, 8>(a, lane);
                *reinterpret_cast<float2*>(&red_s[w][(lane & 7) * 8 + (lane >> 3) * 2]) = make_float2(a[0], a[1]);
                bar_sync<3, 256>();
                if (w == 0) {
                    float q0 = 0.f, q1 = 0.f;
#pragma unroll
                    for (int i = 0; i < 8; i++) { const float2 v = *reinterpret_cast<const float2*>(&red_s[i][2 * lane]); q0 += v.x; q1 += v.y; }
                    stg_pub2(&p.s->qbox[cl][r * 64 + 2 * lane], __float_as_uint(rbf(q0)) | tag, __float_as_uint(rbf(q1)) | tag);
                }
            }
            mbar_wait(bar0 + B_Q * 8, 0);
            const uint32_t qa0 = s2u(&q_s[0][0]) + (g & 1) * 512 + tq4 * 16 + (((g >> 1) ^ g) & 1) * 64, qa1 = qa0 ^ 64;
            const uint32_t ka0 = sm0 + (w & 1) * 8192 + g * 512 + tq4 * 16 + (g & 1) * 64;
            const uint32_t sa = s2u(&sc_s[(w & 1) * 16 + g]);
#pragma unroll 1
            for (int i4 = 0; i4 < 4; i4++) {
                const int tile = (w >> 1) + 4 * i4, it = IT_K + tile;
                const int slot = it >= NS ? it - NS : it;
                uint4 qf[8];
#pragma unroll
                for (int i = 0; i < 8; i++) qf[i] = lds128((i & 1 ? qa1 : qa0) + (tile >> 1) * 1024 + (i >> 1) * 128);
                mbar_wait(bar0 + (B_FULL + it) * 8, 0);
                float ca[4] = {0.f, 0.f, 0.f, 0.f}, cb[4] = {0.f, 0.f, 0.f, 0.f};
                const uint32_t base0 = ka0 + slot * TILE, base1 = base0 ^ 64;
#pragma unroll
                for (int i = 0; i < 8; i++) {
                    const uint32_t a = (i & 1 ? base1 : base0) + (i >> 1) * 128;
                    const uint4 lo = lds128(a), hi = lds128(a + 4096);
                    mma16816(ca, lo.x, hi.x, lo.y, hi.y, qf[i].x, qf[i].y);
                    mma16816(cb, lo.z, hi.z, lo.w, hi.w, qf[i].z, qf[i].w);
                }
                if (lane == 0) mbar_arrive(bar0 + (B_EMPTY + slot) * 8, 4);
                if (tq4 == (g & 1)) {
                    const uint32_t s0 = pack_bf(ca[0] + cb[0], ca[1] + cb[1]), s1 = pack_bf(ca[2] + cb[2], ca[3] + cb[3]);
                    sts64f(sa + tile * 256, bflo(s0) * 0.0625f, bfhi(s0) * 0.0625f);
                    sts64f(sa + tile * 256 + 64, bflo(s1) * 0.0625f, bfhi(s1) * 0.0625f);
                }
            }
            bar_sync<3, 256>();
            {
                float4 s = *reinterpret_cast<const float4*>(&sc_s[2 * t]);
                float m0 = fmaxf(s.x, s.z), m1 = fmaxf(s.y, s.w);
#pragma unroll
                for (int o = 16; o; o >>= 1) { m0 = fmaxf(m0, __shfl_xor_sync(0xffffffffu, m0, o)); m1 = fmaxf(m1, __shfl_xor_sync(0xffffffffu, m1, o)); }
                s.x = exp2f((s.x - m0) * LOG2E); s.y = exp2f((s.y - m1) * LOG2E);
                s.z = exp2f((s.z - m0) * LOG2E); s.w = exp2f((s.w - m1) * LOG2E);
                const int pos = (t & ~15) + (t & 3) * 4 + ((t >> 2) & 3);
                p_s[0][pos] = pack_bf(s.x, s.z);
                p_s[1][pos] = pack_bf(s.y, s.w);
                float l0 = s.x + s.z, l1 = s.y + s.w;
#pragma unroll
                for (int o = 16; o; o >>= 1) { l0 += __shfl_xor_sync(0xffffffffu, l0, o); l1 += __shfl_xor_sync(0xffffffffu, l1, o); }
                cluster_wait();
                if (lane < 8) st_async2(mapa(s2u(&ml_s[w][r]), lane), __float_as_uint(lane < 4 ? m0 : m1), __float_as_uint(lane < 4 ? l0 : l1), mapa(bar0 + B_ML * 8, lane));
                bar_sync<3, 256>();
            }
            {
                const uint32_t lo = sm0 + (w >> 1) * 1024 + (lane & 7) * 128 + (lane >> 4) * 4096;
                const uint32_t sw = ((w & 1) * 4 + ((lane >> 3) & 1)) ^ (lane & 7);
                const uint32_t pa = s2u(&p_s[g & 1][tq4 * 4]);
                const int dst = (tq4 & 1) * 4 + (w >> 1);
                const uint32_t da = mapa(s2u(&in_s[0][r][(w & 1) * 32 + (tq4 >> 1) * 16 + g]), dst), db = mapa(bar0 + B_O * 8, dst);
                int slot = IT_V - NS;
#pragma unroll 1
                for (int h = 0; h < 8; h++) {
                    float acc[4][4];
#pragma unroll
                    for (int i = 0; i < 4; i++) { acc[i][0] = acc[i][1] = acc[i][2] = acc[i][3] = 0.f; }
#pragma unroll
                    for (int j = 0; j < 2; j++) {
                        const uint4 pf = lds128(pa + (2 * h + j) * 64);
                        const uint32_t base = lo + (slot + j) * TILE;
                        mbar_wait(bar0 + (B_FULL + IT_V + 2 * h + j) * 8, 0);
                        uint4 vf[4];
#pragma unroll
                        for (int i = 0; i < 4; i++) vf[i] = ldsm4t(base + (i >> 1) * 8192 + ((sw ^ (2 * (i & 1))) << 4));
                        mma16816(acc[0], vf[0].x, vf[0].y, vf[0].z, vf[0].w, pf.x, pf.y);
                        mma16816(acc[1], vf[1].x, vf[1].y, vf[1].z, vf[1].w, pf.x, pf.y);
                        mma16816(acc[2], vf[2].x, vf[2].y, vf[2].z, vf[2].w, pf.z, pf.w);
                        mma16816(acc[3], vf[3].x, vf[3].y, vf[3].z, vf[3].w, pf.z, pf.w);
                        if (lane == 0) mbar_arrive(bar0 + (B_EMPTY + slot + j) * 8, 1);
                    }
                    slot += 2;
                    if (slot == NS) slot = 0;
                    const bool hi = tq4 & 2, h1 = tq4 & 1;
                    const float x0 = hi ? acc[1][0] + acc[3][0] : acc[0][0] + acc[2][0], x1 = hi ? acc[1][1] + acc[3][1] : acc[0][1] + acc[2][1];
                    const float x2 = hi ? acc[1][2] + acc[3][2] : acc[0][2] + acc[2][2], x3 = hi ? acc[1][3] + acc[3][3] : acc[0][3] + acc[2][3];
                    st_async1(da + h * 2048, __float_as_uint(h1 ? x1 : x0), db + h * 8);
                    st_async1(da + h * 2048 + 32, __float_as_uint(h1 ? x3 : x2), db + h * 8);
                }
            }
        } else {
            const int k = cl - 8;
            if (w == 0) stg_pub1(&p.s->hbox[r][k * 32 + lane], tag ^ 2u);
            {
                float a[8];
#pragma unroll
                for (int i = 0; i < 8; i++) a[i] = 0.f;
                mbar_wait(bar0, 0);
#pragma unroll 1
                for (int i = 0; i < 7; i++) fma8(a, lds128(sm0 + (t + 256 * i) * 16), xn_s[(t >> 2) + 64 * i]);
                halve<8, 16>(a, lane); halve<4, 8>(a, lane); halve<2, 4>(a, lane);
                red_s[w][(lane & 3) * 8 + (lane >> 2)] = a[0];
                bar_sync<3, 256>();
                if (w == 0) {
                    float h = 0.f;
#pragma unroll
                    for (int i = 0; i < 8; i++) h += red_s[i][lane];
                    h = rbf(rbf(h) + b1_s[lane]);
                    const float u = 0.7978845608028654f * (h + 0.044715f * h * h * h);
                    stg_pub1(&p.s->hbox[r][k * 32 + lane], __float_as_uint(rbf(0.5f * h * (1.f + tanhf(u)))) | tag);
                }
                if (t < 56) {
                    uint4 v;
                    int it = 0;
                    do { __nanosleep(1000); v = ldg_poll(&p.s->hbox[r][t * 4]); } while (bad4(v, tag) && ++it < SPIN_LIMIT);
                    const int pi = 2 * t, pos = (pi & ~15) + (pi & 3) * 4 + ((pi >> 2) & 3);
                    h_s[pos] = __byte_perm(v.x, v.y, 0x7632);
                    h_s[pos + 4] = __byte_perm(v.z, v.w, 0x7632);
                }
                bar_sync<3, 256>();
            }
            cluster_wait();
            if (w < 6) gather_o(w);
            {
                float acc[2][4] = {{0.f, 0.f, 0.f, 0.f}, {0.f, 0.f, 0.f, 0.f}};
                const uint32_t base = sm0 + SM_W2 + ((lane & 7) + 16 * ((lane >> 3) & 1) + 8 * (lane >> 4)) * 128 + ((w ^ (lane & 7)) << 4);
                const uint32_t va = s2u(&h_s[tq4 * 4 + (g & 1) * 2]);
                const uint32_t da = mapa(s2u(&in_s[0][0][(32 + r) * 8 + g]), w), db = mapa(bar0 + B_F * 8, w);
                uint4 u0, u1;
                float2 b0, b1;
#pragma unroll
                for (int i = 0; i < 15; i++) {
                    uint4 n0, n1;
                    float2 c0, c1;
                    if (i == 13) {
                        mma16816(acc[0], u0.x, u0.y, u0.z, u0.w, __float_as_uint(b0.x), __float_as_uint(b0.y));
                        mma16816(acc[1], u1.x, u1.y, u1.z, u1.w, __float_as_uint(b1.x), __float_as_uint(b1.y));
                    }
                    if (i < 14) {
                        if (i == 7 || i == 13) mbar_wait(bar0 + (i == 7 ? B_O05 : B_O6) * 8, 0);
                        const int j = i < 7 ? i : 2 * i - 7;
                        c0 = lds64f(va + j * 64);
                        if (i >= 7) c1 = lds64f(va + j * 64 + 64);
                        mbar_wait(bar0 + (1 + i) * 8, 0);
                        n0 = ldsm4t(base + (i < 7 ? j : j + 1) * 4096);
                        if (i >= 7) n1 = ldsm4t(base + (j + 2) * 4096);
                    }
                    if (i > 0 && i != 13) {
                        mma16816(acc[i > 7 ? 0 : i & 1], u0.x, u0.y, u0.z, u0.w, __float_as_uint(b0.x), __float_as_uint(b0.y));
                        if (i > 7) mma16816(acc[1], u1.x, u1.y, u1.z, u1.w, __float_as_uint(b1.x), __float_as_uint(b1.y));
                    }
                    u0 = n0; u1 = n1; b0 = c0; b1 = c1;
                }
                if (tq4 == 0) st_async1(da, __float_as_uint((acc[0][0] + acc[0][3]) + (acc[1][0] + acc[1][3])), db);
            }
        }
    } else {
        const int fw = warp - 9, t = threadIdx.x - 288;
        if (fw == 0) {
            if (elect()) {
#pragma unroll
                for (int i = IT_K + 1; i < NBAR; i++) mbar_init(bar0 + i * 8, (i >= B_EMPTY && i < B_Q) ? 8 : 1);
                mbar_fence_init();
            }
            __syncwarp();
            bar_arrive<2, 64>();
            if (elect()) {
                mbar_expect(bar0 + B_Q * 8, 8192);
                mbar_expect(bar0 + B_ML * 8, strm ? 512 : 1024);
                mbar_expect(bar0 + B_F * 8, 256);
#pragma unroll
                for (int i = 0; i < 8; i++) mbar_expect(bar0 + (B_O + i) * 8, 2048);
            }
            __syncwarp();
        } else if (fw == 1) {
            uint32_t e;
            asm volatile("ld.relaxed.gpu.global.u32 %0, [%1];" : "=r"(e) : "l"(&p.s->epoch) : "memory");
            if (lane == 0) ep_s = e;
        } else if (!strm) {
            if (fw == 2) {
                b1_s[lane] = __bfloat162float(p.b1[(c - 64) * 32 + lane]);
            } else if (fw == 3) {
                const int col = (c - 64) * 8 + (lane & 7);
                if (lane < 8) b1_s[32 + lane] = __bfloat162float(p.x[col]) + __bfloat162float(p.b2[col]);
            }
        }
        bar_sync<1, NTHREADS>();
        cluster_arrive();
        const uint32_t tag = (ep_s + 1) & 3u;
        if (fw == 4) {
            if (!strm) gather_o(6);
        } else if (strm) {
            {
                uint4 v;
                int it = 0;
                mbar_wait(bar0 + (B_EMPTY + 3) * 8, 0);
                while (true) {
                    __nanosleep(it ? 150 : 500);
                    v = ldg_poll(&p.s->qbox[r][t * 4]);
                    if (!bad4(v, tag) || ++it >= SPIN_LIMIT) break;
                }
                __syncwarp();
                cluster_wait();
                const uint32_t lo = __byte_perm(v.x, v.y, 0x7632), hi = __byte_perm(v.z, v.w, 0x7632);
#pragma unroll
                for (int d = 0; d < 8; d++) st_async2(mapa(s2u(&q_s[r][(t * 2) ^ ((t >> 6) * 16)]), d), lo, hi, mapa(bar0 + B_Q * 8, d));
            }
            if (fw == 0) {
                uint32_t* dst = &p.s->obox[0][r][cl][(lane >> 3) * 16 + (lane & 3) * 4 + ((lane >> 2) & 1) * 2];
#pragma unroll
                for (int h = 0; h < 8; h++) stg_pub2(dst + h * 4096, tag ^ 2u, tag ^ 2u);
                if ((lane & 7) == 0) { stg_pub2(&p.s->sbox[r][cl][2 * (lane >> 3)], tag ^ 2u, tag ^ 2u); stg_pub2(&p.s->sbox[r][cl][2 * (lane >> 3) + 8], tag ^ 2u, tag ^ 2u); }
                mbar_wait(bar0 + B_ML * 8, 0);
                float e[2];
#pragma unroll
                for (int i = 0; i < 2; i++) {
                    const float2 v = ml_s[(lane >> 3) + 4 * i][lane & 7];
                    float M = v.x;
#pragma unroll
                    for (int o = 1; o < 8; o <<= 1) M = fmaxf(M, __shfl_xor_sync(0xffffffffu, M, o));
                    e[i] = exp2f((v.x - M) * LOG2E);
                    float L = v.y * e[i];
#pragma unroll
                    for (int o = 1; o < 8; o <<= 1) L += __shfl_xor_sync(0xffffffffu, L, o);
                    if ((lane & 7) == 0) stg_pub2(&p.s->sbox[r][cl][2 * ((lane >> 3) + 4 * i)], tagf(M, tag), tagf(L, tag));
                }
#pragma unroll 1
                for (int h = 0; h < 8; h++) {
                    float ws[8];
#pragma unroll
                    for (int s = 0; s < 8; s++) ws[s] = __shfl_sync(0xffffffffu, h < 4 ? e[0] : e[1], (h & 3) * 8 + s);
                    mbar_wait(bar0 + (B_O + h) * 8, 0);
                    float2 ov[8];
#pragma unroll
                    for (int s = 0; s < 8; s++) ov[s] = lds64f(s2u(&in_s[h][s][2 * lane]));
                    const float o0 = (fmaf(ov[0].x, ws[0], ov[1].x * ws[1]) + fmaf(ov[2].x, ws[2], ov[3].x * ws[3])) + (fmaf(ov[4].x, ws[4], ov[5].x * ws[5]) + fmaf(ov[6].x, ws[6], ov[7].x * ws[7]));
                    const float o1 = (fmaf(ov[0].y, ws[0], ov[1].y * ws[1]) + fmaf(ov[2].y, ws[2], ov[3].y * ws[3])) + (fmaf(ov[4].y, ws[4], ov[5].y * ws[5]) + fmaf(ov[6].y, ws[6], ov[7].y * ws[7]));
                    stg_pub2(dst + h * 4096, tagf(o0, tag), tagf(o1, tag));
                }
            }
        } else {
            const int g = lane >> 2, tq4 = lane & 3;
            const uint32_t g0 = g0_s;
            while (gtime() - g0 < p.ts) __nanosleep(300);
            float wgt[2];
            {
                uint4 v;
                int it = 0;
                while (true) {
                    v = ldg_poll(&p.s->sbox[r][g][4 * tq4]);
                    if (!__any_sync(0xffffffffu, bad4(v, tag)) || ++it >= SPIN_LIMIT) break;
                    __nanosleep(300);
                }
#pragma unroll
                for (int i = 0; i < 2; i++) {
                    const float m = __uint_as_float((i ? v.z : v.x) & ~3u);
                    float M = m;
#pragma unroll
                    for (int o = 4; o < 32; o <<= 1) M = fmaxf(M, __shfl_xor_sync(0xffffffffu, M, o));
                    const float e = exp2f((m - M) * LOG2E);
                    float L = __uint_as_float((i ? v.w : v.y) & ~3u) * e;
#pragma unroll
                    for (int o = 4; o < 32; o <<= 1) L += __shfl_xor_sync(0xffffffffu, L, o);
                    wgt[i] = __fdividef(e, L);
                }
                if (fw == 0) {
                    ml_s[2 * tq4][g].x = wgt[0]; ml_s[2 * tq4 + 1][g].x = wgt[1];
                    __syncwarp();
                    if (lane == 0) mbar_arrive(bar0 + B_WGT * 8, 1);
                }
            }
            const uint32_t fa = s2u(&in_s[0][0][(r * 4 + fw) * 8 + g]);
            const uint32_t da0 = mapa(fa, 2 * tq4), db0 = mapa(bar0 + B_F7 * 8, 2 * tq4), da1 = mapa(fa, 2 * tq4 + 1), db1 = mapa(bar0 + B_F7 * 8, 2 * tq4 + 1);
            const float wg7 = __shfl_sync(0xffffffffu, wgt[1], (lane & 28) + 3);
            cluster_wait();
            mbar_wait(bar0 + 15 * 8, 0);
            uint4 wf[4];
#pragma unroll
            for (int j = 0; j < 4; j++)
                wf[j] = ldsm4t(sm0 + SM_WO + 7 * 8192 + fw * 2048 + ((lane & 7) + 8 * (lane >> 4)) * 128 + (((2 * j + ((lane >> 3) & 1)) ^ (lane & 7)) << 4));
            const uint32_t* src = &p.s->obox[7][r][g][fw * 16 + tq4 * 4];
            uint4 ov;
            {
                while (gtime() - g0 < p.to7) __nanosleep(64);
                int it = 0;
                do { ov = ldg_poll(src); } while (__any_sync(0xffffffffu, bad4(ov, tag)) && ++it < SPIN_LIMIT);
            }
            const uint32_t b0 = pack_bf(__uint_as_float(ov.x) * wg7, __uint_as_float(ov.y) * wg7), b1 = pack_bf(__uint_as_float(ov.z) * wg7, __uint_as_float(ov.w) * wg7);
            float a[8];
#pragma unroll
            for (int j = 0; j < 4; j++) {
                float acc[4] = {0.f, 0.f, 0.f, 0.f};
                mma16816(acc, wf[j].x, wf[j].y, wf[j].z, wf[j].w, b0, b1);
                a[2 * j] = acc[0] + acc[1]; a[2 * j + 1] = acc[2] + acc[3];
            }
            halve<8, 2>(a, lane); halve<4, 1>(a, lane);
            st_async1(da0, __float_as_uint(a[0]), db0);
            st_async1(da1, __float_as_uint(a[1]), db1);
            if (fw == 0) {
                const float base = b1_s[32 + (lane & 7)];
                __nv_bfloat16* dst = p.out + (c - 64) * 8 + (lane & 7);
                const volatile float* in = &in_s[0][0][0];
                float s[8];
                mbar_wait(bar0 + B_F7 * 8, 0);
#pragma unroll
                for (int i = 0; i < 8; i++) s[i] = in[i * 32 + lane];
                float v = ((s[0] + s[1]) + (s[2] + s[3])) + ((s[4] + s[5]) + (s[6] + s[7]));
                v += __shfl_xor_sync(0xffffffffu, v, 8);
                v += __shfl_xor_sync(0xffffffffu, v, 16);
                v += base;
                mbar_wait(bar0 + B_F * 8, 0);
#pragma unroll
                for (int i = 0; i < 8; i++) s[i] = in[256 + i * 8 + (lane & 7)];
                v += ((s[0] + s[1]) + (s[2] + s[3])) + ((s[4] + s[5]) + (s[6] + s[7]));
                if (lane < 8) *dst = __float2bfloat16_rn(v);
                if (c == 64 && lane == 0) p.s->epoch = ep_s + 1;
            }
        }
    }
}

typedef CUresult (*EncodeFn)(CUtensorMap*, CUtensorMapDataType, cuuint32_t, void*, const cuuint64_t*, const cuuint64_t*,
                             const cuuint32_t*, const cuuint32_t*, CUtensorMapInterleave, CUtensorMapSwizzle,
                             CUtensorMapL2promotion, CUtensorMapFloatOOBfill);

void make_map(EncodeFn encode, CUtensorMap* m, void* base, uint64_t cols, uint64_t rows, uint32_t bc, uint32_t br, bool swz) {
    cuuint64_t gd[2] = {cols, rows}; cuuint64_t gs[1] = {cols * 2}; cuuint32_t bd[2] = {bc, br}; cuuint32_t es[2] = {1, 1};
    encode(m, CU_TENSOR_MAP_DATA_TYPE_BFLOAT16, 2, base, gd, gs, bd, es, CU_TENSOR_MAP_INTERLEAVE_NONE,
           swz ? CU_TENSOR_MAP_SWIZZLE_128B : CU_TENSOR_MAP_SWIZZLE_NONE, CU_TENSOR_MAP_L2_PROMOTION_L2_128B, CU_TENSOR_MAP_FLOAT_OOB_FILL_NONE);
}

}

static const uint32_t g_cfg[10] = {5140, 1500, 500, 9300, 11625, 1400, 2450, 13020, 13420, 650};

extern "C" void kernel_launch(void* const* d_in, const int* in_sizes, int n_in, void* d_out, int out_size) {
    (void)in_sizes; (void)n_in; (void)out_size;
    static EncodeFn encode = nullptr;
    static Scratch* scratch = nullptr;
    static double f = 1.0;
    if (!encode) {
        void* fn = nullptr;
        cudaDriverEntryPointQueryResult st;
        cudaGetDriverEntryPoint("cuTensorMapEncodeTiled", &fn, cudaEnableDefault, &st);
        encode = (EncodeFn)fn;
        cudaGetSymbolAddress((void**)&scratch, g_scratch);
        int dev = 0, khz = 0, bits = 0;
        cudaGetDevice(&dev);
        cudaDeviceGetAttribute(&khz, cudaDevAttrMemoryClockRate, dev);
        cudaDeviceGetAttribute(&bits, cudaDevAttrGlobalMemoryBusWidth, dev);
        if (khz > 0 && bits > 0) f = (2619000.0 * 5120.0) / ((double)khz * bits);
        cudaFuncSetAttribute(fused_decode_kernel, cudaFuncAttributeMaxDynamicSharedMemorySize, SM_DYN);
    }
    CUtensorMap tq, t1, t2, tv, to;
    make_map(encode, &tq, d_in[3], 4096, D_MODEL, 64, 128, false);
    make_map(encode, &t1, d_in[6], FFN, D_MODEL, 32, 224, false);
    make_map(encode, &t2, d_in[8], D_MODEL, FFN, 64, 32, true);
    make_map(encode, &to, d_in[4], D_MODEL, 4096, 64, 64, true);
    {
        cuuint64_t gd[4] = {64, 8, 4, (cuuint64_t)SK}; cuuint64_t gs[3] = {512, 128, 4096}; cuuint32_t bd[4] = {64, 8, 4, 4}; cuuint32_t es[4] = {1, 1, 1, 1};
        encode(&tv, CU_TENSOR_MAP_DATA_TYPE_BFLOAT16, 4, d_in[2], gd, gs, bd, es, CU_TENSOR_MAP_INTERLEAVE_NONE,
               CU_TENSOR_MAP_SWIZZLE_128B, CU_TENSOR_MAP_L2_PROMOTION_NONE, CU_TENSOR_MAP_FLOAT_OOB_FILL_NONE);
    }
    Params p;
    p.x = (const __nv_bfloat16*)d_in[0];
    p.k = (const char*)d_in[1];
    p.b1 = (const __nv_bfloat16*)d_in[7];
    p.b2 = (const __nv_bfloat16*)d_in[9];
    p.out = (__nv_bfloat16*)d_out;
    p.s = scratch;
    auto sc = [&](int i, double fixed) { return (uint32_t)(fixed + (g_cfg[i] - fixed) * f + 0.5); };
    p.pace = sc(0, 0); p.t0 = sc(1, 0); p.tw1 = sc(2, 0); p.ts = sc(3, 2000); p.tw2 = sc(4, 0); p.pace_w2 = sc(5, 0); p.pace_wo = sc(6, 0);
    p.to6 = sc(7, 1500); p.to7 = sc(8, 1300); p.th = sc(9, 0);
    fused_decode_kernel<<<NCTA, NTHREADS, SM_DYN, cudaStreamPerThread>>>(p, tq, t1, t2, tv, to);
}
```
